```python
import torch

def _softmax(x, axis=-1):
    return torch.softmax(x, dim=axis)
def _gelu(x):
    return torch.nn.functional.gelu(x, approximate="tanh")
def _silu(x):
    return torch.nn.functional.silu(x)
def _sigmoid(x):
    return torch.sigmoid(x)
def _layernorm(x, axis=-1, eps=1e-5):
    m = x.mean(dim=axis, keepdim=True)
    v = x.var(dim=axis, keepdim=True, unbiased=False)
    return (x - m) / torch.sqrt(v + eps)
def _scatter_add(tgt, idx, src, axis=0):
    return tgt.clone().index_add_(axis, idx, src)
def _segment_sum(src, seg, n):
    out = torch.zeros((n,) + src.shape[1:], dtype=src.dtype)
    return out.index_add_(0, seg, src)
def _pad(x, pw):
    flat = tuple(v for pair in reversed(pw) for v in pair)
    return torch.nn.functional.pad(x, flat)

kernel_name = 'interleave_layers__gqa_block_cached__glu_gated_bilinear__decode'

def setup_inputs():

    _w = (lambda a: (lambda t: t.to(torch.bfloat16) if t.is_floating_point() else t)(torch.as_tensor(a)))
    def _A_setup():
        B, Sq, D = 2, 1, 512
        Hq, Hkv, Sk, Dh = 32, 32, 16384, 128
        assert Hq % Hkv == 0, (Hq, Hkv)
        return {
            "x": _w((lambda *s: torch.randn(*s, dtype=torch.bfloat16) * 0.05)(B, Sq, D)),
            "k_cache": _w((lambda *s: torch.randn(*s, dtype=torch.bfloat16) * 0.8)(B, Hkv, Sk, Dh)),
            "v_cache": _w((lambda *s: torch.randn(*s, dtype=torch.bfloat16) * 1.6)(B, Hkv, Sk, Dh)),
            "wq": _w((lambda *s: torch.randn(*s, dtype=torch.bfloat16) * 0.8)(D, Hq * Dh) * (D ** -0.5)),
            "wo": _w((lambda *s: torch.randn(*s, dtype=torch.bfloat16) * 1.6)(Hq * Dh, D) * ((Hq * Dh) ** -0.5)),
        }
    _A_in = _A_setup()

    def _B_setup():
        B, S, D, F = 2, 1, 512, 1376
        return {
            "x": _w((lambda *s: torch.randn(*s, dtype=torch.bfloat16) * 0.05)(B, S, D)),
            "w_gate": _w((lambda *s: torch.randn(*s, dtype=torch.bfloat16) * 0.4)(D, F) * (D ** -0.5)),
            "w_up": _w((lambda *s: torch.randn(*s, dtype=torch.bfloat16) * 0.4)(D, F) * (D ** -0.5)),
            "w_down": _w((lambda *s: torch.randn(*s, dtype=torch.bfloat16) * 0.4)(F, D) * (F ** -0.5)),
        }
    _B_in = _B_setup()

    return {
        "A_x": _A_in["x"],
        "A_k_cache": _A_in["k_cache"],
        "A_v_cache": _A_in["v_cache"],
        "A_wq": _A_in["wq"],
        "A_wo": _A_in["wo"],
        "B_x": _B_in["x"],
        "B_w_gate": _B_in["w_gate"],
        "B_w_up": _B_in["w_up"],
        "B_w_down": _B_in["w_down"],
    }

def reference(A_x, A_k_cache, A_v_cache, A_wq, A_wo, B_x, B_w_gate, B_w_up, B_w_down):
    def _A_ref(x, k_cache, v_cache, wq, wo):
        B, Sq, D = x.shape
        Hq, Dh = 32, 128
        Hkv = k_cache.shape[1]
        rep = Hq // Hkv
        q = (lambda x, *d: x.permute(*d))((x @ wq).reshape(B, Sq, Hq, Dh), 0, 2, 1, 3)
        k = (lambda x, n, axis: torch.repeat_interleave(x, n, dim=axis))(k_cache, rep, axis=1)
        v = (lambda x, n, axis: torch.repeat_interleave(x, n, dim=axis))(v_cache, rep, axis=1)
        scores = torch.einsum("bhqd,bhkd->bhqk", q, k) * (Dh ** -0.5)
        p = _softmax(scores, axis=-1)
        o = torch.einsum("bhqk,bhkd->bhqd", p, v)
        return (lambda x, *d: x.permute(*d))(o, 0, 2, 1, 3).reshape(B, Sq, Hq * Dh) @ wo

    def _B_ref(x, w_gate, w_up, w_down):
        g = torch.einsum("bsd,df->bsf", x, w_gate)
        u = torch.einsum("bsd,df->bsf", x, w_up)
        h = g * u
        return torch.einsum("bsf,fd->bsd", h, w_down)

    x = A_x
    x = x + _A_ref(_layernorm(x, axis=-1), A_k_cache, A_v_cache, A_wq, A_wo)
    x = x + _B_ref(_layernorm(x, axis=-1), B_w_gate, B_w_up, B_w_down)
    x = x + _A_ref(_layernorm(x, axis=-1), A_k_cache, A_v_cache, A_wq, A_wo)
    x = x + _B_ref(_layernorm(x, axis=-1), B_w_gate, B_w_up, B_w_down)
    return x
```

```cpp
#include <cuda_runtime.h>
#include <cuda_bf16.h>
#include <cuda.h>
#include <stdint.h>

namespace {

constexpr int DM = 512;
constexpr int NH = 32;
constexpr int SK = 16384;
constexpr int FF = 1376;
constexpr int TPH = SK / 8;
constexpr int TPB = NH * TPH;

#define CFG_RP 5
#define CFG_REG_S 208
#define CFG_REG_A 88
#define CFG_Q 112
#define CFG_IDLE 0
#define CFG_IDLE_WAIT 0
#define CFG_HINT_SLEEP 20
#define CFG_SLOTS 3
#define CFG_SIDE_MAX 1
#define CFG_HT 56
constexpr int RP = CFG_RP;
constexpr int NMAIN = 128;
constexpr int NHELP = 4;
constexpr int S_HELP_W = CFG_SLOTS == 3 ? 5 : 4;
constexpr int NGRP = FF / 8;
constexpr int NGRP2 = NGRP - NMAIN;

constexpr uint32_t SMEM_BYTES = 232448;
constexpr uint32_t OFF_RING = 0;
constexpr uint32_t RING_W = CFG_SLOTS * 2048;
constexpr uint32_t OFF_MISC = 8 * RING_W;
constexpr uint32_t OFF_RBAR = OFF_MISC;
constexpr uint32_t OFF_SBAR = OFF_RBAR + 32 * 8;
constexpr uint32_t OFF_CBAR = OFF_SBAR + 40 * 8;
constexpr uint32_t BAR_Q1 = OFF_CBAR + 0, BAR_R0 = OFF_CBAR + 8, BAR_R1 = OFF_CBAR + 16;
constexpr uint32_t BAR_P0 = OFF_CBAR + 24;
constexpr uint32_t OFF_CTR = OFF_CBAR + 56;
constexpr uint32_t OFF_HELD = OFF_CTR + 96;
constexpr uint32_t OFF_WP = OFF_MISC + 768;
constexpr uint32_t OFF_QF = OFF_WP + 256;
constexpr uint32_t OFF_PART = OFF_QF + 512;
constexpr uint32_t OFF_XN = OFF_PART + 8 * 132 * 4;
constexpr uint32_t OFF_RED = OFF_XN + 1024;
constexpr uint32_t OFF_SEG = OFF_RED + 64;
constexpr uint32_t OFF_W = OFF_MISC + 7168;
constexpr uint32_t OFF_WQ = OFF_W;
constexpr uint32_t OFF_WO = OFF_WQ + 32768;
constexpr uint32_t OFF_WF = OFF_WO + 32768;
constexpr uint32_t WF_BYTES = 24576;
constexpr uint32_t OFF_QF_HELP = OFF_W;
static_assert(OFF_HELD + 32 <= OFF_WP, "smem map");
static_assert(OFF_SEG + 112 <= OFF_W && OFF_W % 1024 == 0 && OFF_WF % 1024 == 0, "smem map");
constexpr uint32_t SC_RED4 = OFF_PART;
constexpr uint32_t SC_XN1 = OFF_PART + 1024;
constexpr uint32_t SC_O = OFF_PART + 2048;
constexpr uint32_t SC_H = OFF_PART + 2560;

__device__ unsigned long long g_P[2][NH][5][132];
__device__ unsigned long long g_Z[2][NH][DM];
__device__ unsigned long long g_X1[2][DM];
__device__ unsigned long long g_D[2][NMAIN][DM];
__device__ unsigned long long g_X2[2][DM];
__device__ unsigned long long g_Q[2][NH][128];
__device__ unsigned int g_epoch;
__device__ unsigned int g_cntP[2][NH], g_cntQ[2][NH], g_cntZ[2][4], g_cntX1[2], g_cntD[2], g_cntX2[2];

struct Params {
  const __nv_bfloat16* x;
  const __nv_bfloat16* wq;
  const __nv_bfloat16* wo;
  const __nv_bfloat16* wg;
  const __nv_bfloat16* wu;
  const __nv_bfloat16* wd;
  __nv_bfloat16* out;
  int ht;
  int q;
  uint32_t zero;
};

constexpr uint32_t D_TILE = 0x1FFFFu;
constexpr uint32_t D_B0 = 1u << 17, D_B1 = 1u << 18;
constexpr uint32_t D_N0 = 1u << 19, D_N1 = 1u << 20;
constexpr uint32_t D_PF = 1u << 21;
constexpr uint32_t D_REG = 1u << 22;
constexpr uint32_t D_PAST0 = 1u << 23, D_PAST1 = 1u << 24, D_PAST2 = 1u << 25;
constexpr uint32_t D_VALID = 1u << 26, D_END = 1u << 27;
constexpr uint32_t D_PASTS = D_PAST0 | D_PAST1 | D_PAST2;
constexpr uint32_t ST_R0 = 1u << 0, ST_R1 = 1u << 1, ST_INJ = 1u << 2, ST_INJ2 = 1u << 3, ST_FL0 = 1u << 7,
                   ST_FL1 = 1u << 8, ST_FL2 = 1u << 9, ST_REGC = 1u << 10, ST_CURB = 1u << 11;
constexpr int SS_F = 0, SS_H0 = 5, SS_H1 = 10, SS_B = 15, SS_K = 20, SS_P = 25;

constexpr uint64_t POL_FIRST = 0x12F0000000000000ull;
constexpr uint64_t POL_NORMAL = 0x16F0000000000000ull;
constexpr float SCALE_LOG2 = 0.08838834764831845f * 1.4426950408889634f;
constexpr int SPIN_LIMIT = 1 << 22;

__device__ __forceinline__ void mbar_init(uint32_t bar, uint32_t cnt) {
  asm volatile("mbarrier.init.shared::cta.b64 [%0], %1;" ::"r"(bar), "r"(cnt) : "memory");
}
__device__ __forceinline__ void mbar_expect_tx(uint32_t bar, uint32_t bytes) {
  asm volatile("mbarrier.arrive.expect_tx.shared::cta.b64 _, [%0], %1;" ::"r"(bar), "r"(bytes) : "memory");
}
__device__ __forceinline__ void mbar_arrive(uint32_t bar) {
  asm volatile("mbarrier.arrive.shared::cta.b64 _, [%0];" ::"r"(bar) : "memory");
}
__device__ __forceinline__ bool mbar_test(uint32_t bar, uint32_t parity) {
  uint32_t ok;
  asm volatile("{\n.reg .pred p;\nmbarrier.test_wait.parity.shared::cta.b64 p, [%1], %2;\nselp.u32 %0, 1, 0, p;\n}"
               : "=r"(ok) : "r"(bar), "r"(parity) : "memory");
  return ok != 0;
}
__device__ __forceinline__ bool mbar_try(uint32_t bar, uint32_t parity) {
  uint32_t ok;
  asm volatile("{\n.reg .pred p;\nmbarrier.try_wait.parity.shared::cta.b64 p, [%1], %2;\nselp.u32 %0, 1, 0, p;\n}"
               : "=r"(ok) : "r"(bar), "r"(parity) : "memory");
  return ok != 0;
}
__device__ __forceinline__ void mbar_wait(uint32_t bar, uint32_t parity) {
  int it = 0;
  while (!mbar_try(bar, parity))
    if (++it > SPIN_LIMIT) __trap();
}
__device__ __forceinline__ void tma_load(uint32_t dst, const CUtensorMap* tm, int c0, int row, uint32_t bar) {
  asm volatile(
      "cp.async.bulk.tensor.2d.shared::cluster.global.tile.mbarrier::complete_tx::bytes.L2::cache_hint"
      " [%0], [%1, {%2, %3}], [%4], %5;" ::"r"(dst), "l"(tm), "r"(c0), "r"(row), "r"(bar), "l"(POL_FIRST)
      : "memory");
}
__device__ __forceinline__ void ldsm4(uint32_t* r, uint32_t addr) {
  asm volatile("ldmatrix.sync.aligned.m8n8.x4.shared.b16 {%0,%1,%2,%3}, [%4];"
               : "=r"(r[0]), "=r"(r[1]), "=r"(r[2]), "=r"(r[3]) : "r"(addr) : "memory");
}
__device__ __forceinline__ void ldsm4t(uint32_t* r, uint32_t addr) {
  asm volatile("ldmatrix.sync.aligned.m8n8.x4.trans.shared.b16 {%0,%1,%2,%3}, [%4];"
               : "=r"(r[0]), "=r"(r[1]), "=r"(r[2]), "=r"(r[3]) : "r"(addr) : "memory");
}
__device__ __forceinline__ void mma16816(float& d0, float& d1, float& d2, float& d3, const uint32_t* a, uint32_t b0,
                                         uint32_t b1) {
  asm("mma.sync.aligned.m16n8k16.row.col.f32.bf16.bf16.f32 {%0,%1,%2,%3}, {%4,%5,%6,%7}, {%8,%9}, {%0,%1,%2,%3};"
      : "+f"(d0), "+f"(d1), "+f"(d2), "+f"(d3)
      : "r"(a[0]), "r"(a[1]), "r"(a[2]), "r"(a[3]), "r"(b0), "r"(b1));
}
__device__ __forceinline__ void mma16816v(float& d0, float& d1, float& d2, float& d3, const uint32_t* a, uint32_t b0,
                                          uint32_t b1) {
  asm volatile("mma.sync.aligned.m16n8k16.row.col.f32.bf16.bf16.f32 {%0,%1,%2,%3}, {%4,%5,%6,%7}, {%8,%9}, {%0,%1,%2,%3};"
               : "+f"(d0), "+f"(d1), "+f"(d2), "+f"(d3)
               : "r"(a[0]), "r"(a[1]), "r"(a[2]), "r"(a[3]), "r"(b0), "r"(b1));
}
__device__ __forceinline__ uint32_t lds32(uint32_t a) {
  uint32_t v;
  asm volatile("ld.shared.u32 %0, [%1];" : "=r"(v) : "r"(a) : "memory");
  return v;
}
__device__ __forceinline__ uint4 lds128(uint32_t a) {
  uint4 v;
  asm volatile("ld.shared.v4.u32 {%0,%1,%2,%3}, [%4];" : "=r"(v.x), "=r"(v.y), "=r"(v.z), "=r"(v.w) : "r"(a) : "memory");
  return v;
}
__device__ __forceinline__ float ldsf(uint32_t a) {
  float v;
  asm volatile("ld.shared.f32 %0, [%1];" : "=f"(v) : "r"(a) : "memory");
  return v;
}
__device__ __forceinline__ void stsf(uint32_t a, float v) {
  asm volatile("st.shared.f32 [%0], %1;" ::"r"(a), "f"(v) : "memory");
}
__device__ __forceinline__ void sts32(uint32_t a, uint32_t v) {
  asm volatile("st.shared.u32 [%0], %1;" ::"r"(a), "r"(v) : "memory");
}
__device__ __forceinline__ void sts16(uint32_t a, uint16_t v) {
  asm volatile("st.shared.u16 [%0], %1;" ::"r"(a), "h"(v) : "memory");
}
__device__ __forceinline__ float ex2(float x) {
  float y;
  asm("ex2.approx.ftz.f32 %0, %1;" : "=f"(y) : "f"(x));
  return y;
}
__device__ __forceinline__ int dep_zero(uint32_t r, uint32_t zero) { return (int)(r & zero); }
__device__ __forceinline__ void tma_issue(uint32_t dst, const CUtensorMap* tm, int c0, int row, uint32_t bar) {
  asm volatile(
      "{\n.reg .pred P;\nelect.sync _|P, 0xffffffff;\n"
      "@P mbarrier.arrive.expect_tx.shared::cta.b64 _, [%4], 2048;\n"
      "@P cp.async.bulk.tensor.2d.shared::cluster.global.tile.mbarrier::complete_tx::bytes.L2::cache_hint"
      " [%0], [%1, {%2, %3}], [%4], %5;\n}" ::"r"(dst), "l"(tm), "r"(c0), "r"(row), "r"(bar), "l"(POL_FIRST)
      : "memory");
}
__device__ __forceinline__ void tma_keep(const CUtensorMap* tm, int row) {
  asm volatile(
      "{\n.reg .pred P;\nelect.sync _|P, 0xffffffff;\n"
      "@P cp.async.bulk.prefetch.tensor.2d.L2.global.tile.L2::cache_hint [%0, {%1, %2}], %3;\n}" ::"l"(tm), "r"(0),
      "r"(row), "l"(POL_NORMAL)
      : "memory");
}
__device__ __forceinline__ void tma_issue2(uint32_t dst, const CUtensorMap* tmK, const CUtensorMap* tmV, int c0, int row,
                                           uint32_t bar) {
  asm volatile(
      "{\n.reg .pred P;\nelect.sync _|P, 0xffffffff;\n"
      "@P mbarrier.arrive.expect_tx.shared::cta.b64 _, [%5], 4096;\n"
      "@P cp.async.bulk.tensor.2d.shared::cluster.global.tile.mbarrier::complete_tx::bytes.L2::cache_hint"
      " [%0], [%1, {%3, %4}], [%5], %6;\n"
      "@P cp.async.bulk.tensor.2d.shared::cluster.global.tile.mbarrier::complete_tx::bytes.L2::cache_hint"
      " [%7], [%2, {%3, %4}], [%5], %6;\n}" ::"r"(dst), "l"(tmK), "l"(tmV), "r"(c0), "r"(row), "r"(bar), "l"(POL_FIRST),
      "r"(dst + 2048)
      : "memory");
}
__device__ __forceinline__ uint32_t uni(uint32_t v) { return __shfl_sync(0xffffffffu, v, 0); }
__device__ __forceinline__ uint32_t atoms_inc_lane0(uint32_t addr, int lane) {
  uint32_t v = 0;
  asm volatile("{\n.reg .pred P;\nsetp.eq.u32 P, %2, 0;\n@P atom.shared.add.u32 %0, [%1], 1;\n}"
               : "+r"(v) : "r"(addr), "r"(lane) : "memory");
  return v;
}
__device__ __forceinline__ uint32_t pack_bf16(float lo, float hi) {
  uint32_t r;
  asm("cvt.rn.bf16x2.f32 %0, %1, %2;" : "=r"(r) : "f"(hi), "f"(lo));
  return r;
}
__device__ __forceinline__ float bf16r(float x) { return __uint_as_float(pack_bf16(0.f, x) & 0xffff0000u); }
__device__ __forceinline__ float bflo(uint32_t w) { return __uint_as_float(w << 16); }
__device__ __forceinline__ float bfhi(uint32_t w) { return __uint_as_float(w & 0xffff0000u); }

__device__ __forceinline__ void ll_st(unsigned long long* p, float v, uint32_t tag) {
  unsigned long long w = ((unsigned long long)tag << 32) | __float_as_uint(v);
  asm volatile("st.relaxed.gpu.global.b64 [%0], %1;" ::"l"(p), "l"(w) : "memory");
}
__device__ __forceinline__ void aux_sync() { asm volatile("bar.sync 1, 128;" ::: "memory"); }
__device__ __forceinline__ void stamp(int) {}
__device__ __forceinline__ void stamp2(int, int) {}

struct Acc { float o0, o1, o2, o3, m, l; };
__device__ __forceinline__ void swapf(float& a, float& b) {
  asm volatile("{\n.reg .f32 t;\nmov.f32 t, %0;\nmov.f32 %0, %1;\nmov.f32 %1, t;\n}" : "+f"(a), "+f"(b));
}

__device__ __forceinline__ uint32_t softmax8(float s0, float s1, float s2, float s3, Acc& a, int lane) {
  const float sc = ((lane & 16) ? (s1 + s2) : (s0 + s3)) * SCALE_LOG2;
  if (__any_sync(0xffffffffu, sc > a.m)) {
    float mx = fmaxf(sc, __shfl_xor_sync(0xffffffffu, sc, 4));
    mx = fmaxf(mx, __shfl_xor_sync(0xffffffffu, mx, 8));
    mx = fmaxf(mx, __shfl_xor_sync(0xffffffffu, mx, 16));
    mx = fmaxf(mx, a.m);
    const float alpha = ex2(a.m - mx);
    a.o0 *= alpha; a.o1 *= alpha; a.o2 *= alpha; a.o3 *= alpha; a.l *= alpha;
    a.m = mx;
  }
  const float p = ex2(sc - a.m);
  a.l += p;
  uint32_t pp, pk;
  asm("cvt.rn.bf16x2.f32 %0, %1, %1;" : "=r"(pp) : "f"(p));
  asm volatile("movmatrix.sync.aligned.m8n8.trans.b16 %0, %1;" : "=r"(pk) : "r"(pp));
  return pk;
}
__device__ __forceinline__ uint32_t qk_reg(const uint32_t* kf, uint32_t qaddr, Acc& a, int lane) {
  float s0 = 0.f, s1 = 0.f, s2 = 0.f, s3 = 0.f;
  {
    const uint4 q = lds128(qaddr);
    mma16816(s0, s1, s2, s3, kf + 0, q.x, q.y);
    mma16816(s0, s1, s2, s3, kf + 4, q.z, q.w);
  }
  {
    const uint4 q = lds128(qaddr + 128);
    mma16816(s0, s1, s2, s3, kf + 8, q.x, q.y);
    mma16816(s0, s1, s2, s3, kf + 12, q.z, q.w);
  }
  return softmax8(s0, s1, s2, s3, a, lane);
}
__device__ __forceinline__ void pv_q(const uint32_t* vf, int j, uint32_t pk, Acc& a, int lane) {
  const int g = lane >> 2;
  const bool cm = ((g & 1) == 0) == ((lane & 2) == 0);
  const bool mine = (g >> 1) == j;
  mma16816(a.o0, a.o1, a.o2, a.o3, vf, (mine && cm) ? pk : 0u, (mine && !cm) ? pk : 0u);
}
__device__ __forceinline__ void pv_reg(const uint32_t* vf, uint32_t pk, Acc& a, int lane) {
#pragma unroll
  for (int j = 0; j < 4; j++) pv_q(vf + 4 * j, j, pk, a, lane);
}

__device__ __forceinline__ void side_fill_w(const CUtensorMap* tmK, const CUtensorMap* tmV, uint32_t sb, uint32_t side,
                                            uint32_t wp, int lane, uint32_t i, uint32_t b, int dep) {
  const uint4 p = lds128(wp + 16);
  const uint32_t slot = uni((p.z & 255) + i * ((p.z >> 8) & 255));
  const int row = (int)(p.y + i * ((p.z >> 16) & 255) + b * TPB) * 16;
  tma_issue2(side + slot * 4096, tmK, tmV, dep, row, sb + OFF_SBAR + slot * 8);
}
__device__ __forceinline__ void stream_prologue(const CUtensorMap* tmK, const CUtensorMap* tmV, const uint32_t sb,
                                                const uint32_t side, const int w, const int lane) {
  const uint32_t ring = sb + OFF_RING + w * RING_W;
  const uint32_t rbar = sb + OFF_RBAR + w * 32;
  const uint32_t wp = sb + OFF_WP + w * 32;
  const uint4 p = lds128(wp + 16);
  const uint32_t nside = p.z >> 24;
  if (lane == 0) {
    mbar_expect_tx(rbar, 2048);      tma_load(ring, tmK, 0, (int)p.w * 16, rbar);
    mbar_expect_tx(rbar + 8, 2048);  tma_load(ring + 2048, tmV, 0, (int)p.w * 16, rbar + 8);
    mbar_expect_tx(rbar + 16, 2048); tma_load(ring + 4096, tmK, 0, (int)(p.w + 1) * 16, rbar + 16);
    if (CFG_SLOTS == 4) { mbar_expect_tx(rbar + 24, 2048); tma_load(ring + 6144, tmV, 0, (int)(p.w + 1) * 16, rbar + 24); }
  }
  __syncwarp();
  side_fill_w(tmK, tmV, sb, side, wp, lane, 0, 0, 0);
  uint32_t sis = 1;
  if (nside > 1) side_fill_w(tmK, tmV, sb, side, wp, lane, sis++, 0, 0);
  int it = 0;
  while (!__all_sync(0xffffffffu, mbar_test(sb + BAR_Q1, 0))) {
    if (sis < nside &&
        __all_sync(0xffffffffu, mbar_test(sb + OFF_SBAR + ((p.z & 255) + (sis - 2) * ((p.z >> 8) & 255)) * 8, 0)))
      side_fill_w(tmK, tmV, sb, side, wp, lane, sis++, 0, 0);
    else
      __nanosleep(40);
    if (++it > SPIN_LIMIT) __trap();
  }
  if (lane == 0) sts32(sb + OFF_HELD + w * 4, sis);
  __syncwarp();
}

__device__ __forceinline__ void stream_warp(const CUtensorMap* tmK, const CUtensorMap* tmV, const uint32_t sb,
                                            const uint32_t side, const int w, const int lane, const uint32_t& zero) {
  const uint32_t ring = sb + OFF_RING + w * RING_W;
  const uint32_t rbar = sb + OFF_RBAR + w * 32;
  const uint32_t wp = sb + OFF_WP + w * 32;
  uint32_t laneK, laneV;
  {
    const int mat = lane >> 3, i = lane & 7;
    const int hk = (mat & 1) ? (i < 4) : (i >= 4);
    const int rk = 2 * i + hk;
    laneK = ring + rk * 128 + (((mat >> 1) ^ (rk & 7)) << 4);
    laneV = laneK ^ (((mat ^ (mat >> 1)) & 1) << 7);
  }
  const uint32_t qoff = lds128(wp + 16).x + (((lane >> 2) & 1) * 4 + (lane & 3)) * 16;

  uint32_t kv[RP][32];
  Acc cur, oth;
  cur.o0 = cur.o1 = cur.o2 = cur.o3 = cur.l = 0.f; cur.m = -INFINITY;
  oth = cur;
  uint32_t st = 0;
  uint32_t csp = 0;
  uint32_t d0, d1;
  uint32_t ev;
  uint32_t ss = 0;
  uint32_t mseg = lds32(wp);
  uint32_t tn = atoms_inc_lane0(lds32(mseg + 12), lane);

  auto ensure = [&](uint32_t b) {
    if (b != ((st & ST_CURB) ? 1u : 0u)) {
      swapf(cur.o0, oth.o0); swapf(cur.o1, oth.o1); swapf(cur.o2, oth.o2); swapf(cur.o3, oth.o3);
      swapf(cur.m, oth.m); swapf(cur.l, oth.l);
      st ^= ST_CURB;
    }
  };
  auto gate = [&](uint32_t b) {
    const uint32_t bit = b ? ST_R1 : ST_R0;
    if (!(st & bit)) { mbar_wait(sb + (b ? BAR_R1 : BAR_R0), 0); st |= bit; }
  };
  auto issue = [&](const CUtensorMap* tm, uint32_t dst, uint32_t bar, uint32_t d, int dep) {
    const int row = (int)(d & D_TILE) * 16;
    tma_issue(dst, tm, dep, row, bar);
    if (d & D_PF) tma_keep(tm, row);
  };
  auto advance = [&]() {
    csp += 2048;
    if ((csp & 0x1800) == 0x1800) csp = (csp & 1) ^ 1;
  };
  auto reg_desc = [&](uint32_t i) { return D_VALID | D_REG | D_B1 | D_PAST0 | (lds128(wp + 16).w + TPB + i); };
  auto grab = [&]() -> uint32_t {
    const uint4 P = lds128(mseg);
    const uint32_t t = __shfl_sync(0xffffffffu, tn, 0);
    uint32_t d;
    bool held = false;
    if (t < P.x) {
      d = P.y + t;
      if (t >= P.z) d |= D_PF;
    } else {
      const uint32_t s0 = lds32(wp);
      while (true) {
        const uint32_t si = (mseg - s0) >> 4;
        if (si >= 4) { d = D_PASTS | D_END; break; }
        const uint4 M = lds128(mseg);
        if (t < M.x) { d = (M.y + t) | (t >= M.z ? D_PF : 0u); break; }
        if (si == 1 && !(st & ST_INJ)) {
          st |= ST_INJ | ST_INJ2;
          ev |= D_VALID;
          held = true;
          d = reg_desc(0);
          break;
        }
        mseg += 16;
      }
    }
    if (held) tn = t; else tn = atoms_inc_lane0(P.w, lane);
    return d;
  };
  auto qk_smem = [&](uint32_t la, uint32_t qa, auto mid) -> uint32_t {
    float s0 = 0.f, s1 = 0.f, s2 = 0.f, s3 = 0.f;
    uint32_t f[8];
    ldsm4(f, la); ldsm4(f + 4, la ^ 32);
    {
      const uint4 q = lds128(qa);
      mma16816v(s0, s1, s2, s3, f, q.x, q.y);
      mma16816v(s0, s1, s2, s3, f + 4, q.z, q.w);
    }
    ldsm4(f, la ^ 64); ldsm4(f + 4, la ^ 96);
    mid(f[7]);
    {
      const uint4 q = lds128(qa + 128);
      mma16816v(s0, s1, s2, s3, f, q.x, q.y);
      mma16816v(s0, s1, s2, s3, f + 4, q.z, q.w);
    }
    return softmax8(s0, s1, s2, s3, cur, lane);
  };
  auto pv_smem = [&](uint32_t la, uint32_t pk, auto mid) {
    const int g = lane >> 2;
    const bool cm = ((g & 1) == 0) == ((lane & 2) == 0);
    const uint32_t b0 = cm ? pk : 0u, b1 = cm ? 0u : pk;
    uint32_t f[8];
    ldsm4t(f, la); ldsm4t(f + 4, la ^ 32);
    mma16816v(cur.o0, cur.o1, cur.o2, cur.o3, f, (g >> 1) == 0 ? b0 : 0u, (g >> 1) == 0 ? b1 : 0u);
    mma16816v(cur.o0, cur.o1, cur.o2, cur.o3, f + 4, (g >> 1) == 1 ? b0 : 0u, (g >> 1) == 1 ? b1 : 0u);
    ldsm4t(f, la ^ 64); ldsm4t(f + 4, la ^ 96);
    mid(f[7]);
    mma16816v(cur.o0, cur.o1, cur.o2, cur.o3, f, (g >> 1) == 2 ? b0 : 0u, (g >> 1) == 2 ? b1 : 0u);
    mma16816v(cur.o0, cur.o1, cur.o2, cur.o3, f + 4, (g >> 1) == 3 ? b0 : 0u, (g >> 1) == 3 ? b1 : 0u);
  };
#define LOG_STEP(kind)
  auto ring_step = [&](const uint32_t d2) {
    csp = uni(csp);
    uint32_t so = csp & 0x1800, bar = rbar + (csp >> 8);
    mbar_wait(bar, csp & 1);
    const uint32_t pk = qk_smem(laneK + so, qoff + ((d0 >> 8) & 256), [&](uint32_t last) {
      if (d1 & D_VALID) issue(tmV, ring + so, bar, d1, dep_zero(last, zero));
    });
    advance();
    so = csp & 0x1800; bar = rbar + (csp >> 8);
    mbar_wait(bar, csp & 1);
    pv_smem(laneV + so, pk, [&](uint32_t last) {
      if (d2 & D_VALID) issue(tmK, ring + so, bar, d2, dep_zero(last, zero));
    });
    LOG_STEP(2u);
    advance();
    d0 = d1; d1 = d2;
  };
  auto reg_step = [&](uint32_t* kf, uint32_t* vf, uint32_t b, bool staticNext, uint32_t dstatic) {
    const uint32_t d2 = staticNext ? dstatic : grab();
    ensure(b);
    csp = uni(csp);
    uint32_t so = csp & 0x1800, bar = rbar + (csp >> 8);
    mbar_wait(bar, csp & 1);
    {
      const uint32_t la = laneK + so;
      ldsm4(kf + 0, la); ldsm4(kf + 4, la ^ 32); ldsm4(kf + 8, la ^ 64); ldsm4(kf + 12, la ^ 96);
      if (d1 & D_VALID) issue(tmV, ring + so, bar, d1, dep_zero(kf[15], zero));
    }
    advance();
    const uint32_t pk = qk_reg(kf, qoff + b * 256, cur, lane);
    so = csp & 0x1800; bar = rbar + (csp >> 8);
    mbar_wait(bar, csp & 1);
    {
      const uint32_t la = laneV + so;
      ldsm4t(vf + 0, la); ldsm4t(vf + 4, la ^ 32); ldsm4t(vf + 8, la ^ 64); ldsm4t(vf + 12, la ^ 96);
      if (d2 & D_VALID) issue(tmK, ring + so, bar, d2, dep_zero(vf[15], zero));
    }
    pv_reg(vf, pk, cur, lane);
    advance();
    d0 = d1; d1 = d2;
  };
  auto flush = [&](uint32_t b, uint32_t area, uint32_t bar) {
    ensure(b);
    float l = cur.l;
    l += __shfl_xor_sync(0xffffffffu, l, 4);
    l += __shfl_xor_sync(0xffffffffu, l, 8);
    l += __shfl_xor_sync(0xffffffffu, l, 16);
    const uint32_t e = area + ((lane & 3) * 16 + (lane >> 2)) * 4;
    stsf(e, cur.o0); stsf(e + 256, cur.o1); stsf(e + 32, cur.o2); stsf(e + 288, cur.o3);
    if (lane == 0) { stsf(area + 512, cur.m); stsf(area + 516, l); }
    __syncwarp();
    if (lane == 0) mbar_arrive(bar);
    cur.o0 = cur.o1 = cur.o2 = cur.o3 = cur.l = 0.f; cur.m = -INFINITY;
  };
  auto side_fill = [&](uint32_t i, uint32_t b, int dep) { side_fill_w(tmK, tmV, sb, side, wp, lane, i, b, dep); };
  auto side_try = [&](const uint32_t j, const bool force) -> bool {
    const uint32_t bit = 1u << j;
    const uint32_t pz = lds128(wp + 16).z;
    const uint32_t slot = uni((pz & 255) + j * ((pz >> 8) & 255));
    const uint32_t bar = sb + OFF_SBAR + slot * 8;
    const uint32_t b = (ss >> (SS_B + j)) & 1;
    bool cyc;
    if (ss & (bit << SS_F)) {
      const uint32_t par = (ss >> (SS_P + j)) & 1;
      if (!force && !__all_sync(0xffffffffu, mbar_test(bar, par))) return false;
      mbar_wait(bar, par);
      cyc = (ss & (bit << SS_K)) != 0;
      ss ^= (bit << SS_F) | (bit << SS_P);
    } else {
      if (!(st & (b ? ST_R1 : ST_R0))) {
        if (!force) return false;
        gate(b);
      }
      cyc = true;
      ss &= ~((bit << SS_H0) | (bit << SS_H1));
    }
    const uint32_t kb = lds32(wp) + 80;
    uint32_t u = 0;
    if (cyc) u = atoms_inc_lane0(lds32(kb + 12) + b * 32, lane);
    ensure(b);
    const uint32_t delta = side + slot * 4096 - ring;
    const uint32_t pk = qk_smem(laneK + delta, qoff + b * 256, [&](uint32_t) {});
    pv_smem(laneV + delta + 2048, pk, [&](uint32_t last) {
      if (cyc) {
        u = __shfl_sync(0xffffffffu, u, 0);
        const int dep = dep_zero(last, zero);
        if (u < lds32(kb)) {
          const int row = (int)(lds32(kb + 4) + b * TPB - u) * 16;
          tma_issue2(ring + delta, tmK, tmV, dep, row, bar);
          ss |= (bit << SS_F) | (bit << SS_K);
        } else if (!b) {
          side_fill(j, 1, dep);
          ss = (ss & ~(bit << SS_K)) | (bit << SS_F) | (bit << SS_B);
        } else {
          ss &= ~(bit << SS_K);
        }
      } else {
        ss |= bit << (b ? SS_H1 : SS_H0);
      }
    });
    LOG_STEP(3u);
    return true;
  };

  ev = 0;
  uint32_t sfull;
  {
    const uint4 p = lds128(wp + 16);
    const uint32_t nside = p.z >> 24;
    sfull = (1u << nside) - 1;
    ss = sfull << SS_F;
    uint32_t sis = lds32(sb + OFF_HELD + w * 4);
    d0 = D_VALID | D_REG | D_B0 | p.w;
    d1 = D_VALID | D_REG | D_B0 | (p.w + 1);
#pragma unroll
    for (int i = 0; i < RP; i++) {
      if (sis < nside) side_fill(sis++, 0, 0);
      reg_step(&kv[i][0], &kv[i][16], 0, i + 2 < RP, D_VALID | D_REG | D_B0 | (lds128(wp + 16).w + i + 2));
    }
    while (sis < nside) side_fill(sis++, 0, 0);
  }
  ev = D_VALID | D_END;
  while (true) {
    uint32_t d2;
    if (d0 & ev) {
      if ((d0 & ev & ~(D_B0 | D_B1)) == 0) {
        ensure((d0 >> 16) & 1);
        ev ^= D_B0 | D_B1;
        d2 = grab();
      } else {
        if (!(st & ST_R0)) {
          if ((st & ST_FL0) && __all_sync(0xffffffffu, mbar_test(sb + BAR_R0, 0))) st |= ST_R0;
        } else if (!(st & ST_R1)) {
          if ((st & ST_FL1) && __all_sync(0xffffffffu, mbar_test(sb + BAR_R1, 0))) st |= ST_R1;
        }
        {
          const uint32_t sF = (ss >> SS_F) & 31, sH0 = (ss >> SS_H0) & 31, sH1 = (ss >> SS_H1) & 31;
          uint32_t need = 0;
          if (!(st & ST_FL0)) { if (d0 & D_PAST0) need = sF; }
          else if (!(st & ST_FL1)) { if (d0 & D_PAST1) need = sfull & ~sH1; }
          else if (d0 & D_END) need = sF | sH0 | sH1;
          const bool force = need != 0;
          uint32_t cand = force ? need : (sF | ((st & ST_R0) ? sH0 : 0u) | ((st & ST_R1) ? sH1 : 0u));
          int budget = force ? 1 : CFG_SIDE_MAX;
          while (cand && budget) {
            const uint32_t j = __ffs(cand) - 1;
            cand &= cand - 1;
            if (side_try(j, force)) budget--;
          }
          if (force) { ev |= D_VALID | D_END; continue; }
        }
        bool redo = true;
        if (!(st & ST_FL0) && (d0 & D_PAST0)) {
          flush(0, sb + OFF_PART + w * 528, sb + BAR_P0);
          st |= ST_FL0;
          if (lane == 0 && w == 0) stamp(10);
        } else if (d0 & D_REG) {
          gate(0);
          if (lane == 0 && w == 0) stamp(11);
#pragma unroll
          for (int i = 0; i < RP; i++) {
            ensure(0);
            const uint32_t pk = qk_reg(&kv[i][0], qoff, cur, lane);
            pv_reg(&kv[i][16], pk, cur, lane);
            reg_step(&kv[i][0], &kv[i][16], 1, i + 2 < RP, reg_desc(i + 2));
          }
        } else if (!(st & ST_FL1) && (d0 & D_PAST1)) {
          flush(1, sb + OFF_PART + w * 528, sb + BAR_P0 + 8);
          st |= ST_FL1;
        } else if (!(st & ST_FL2) && (d0 & D_PAST2)) {
          gate(1);
          flush(0, sb + OFF_PART + w * 528, sb + BAR_P0 + 16);
          st |= ST_FL2;
        } else if (!(st & ST_REGC) && ((st & ST_R1) || (d0 & D_END))) {
          gate(1);
          ensure(1);
#pragma unroll
          for (int i = 0; i < RP; i++) {
            const uint32_t pk = qk_reg(&kv[i][0], qoff + 256, cur, lane);
            pv_reg(&kv[i][16], pk, cur, lane);
          }
          st |= ST_REGC;
        } else if (d0 & D_END) {
          break;
        } else {
          redo = false;
        }
        if (redo) { ev |= D_VALID | D_END; continue; }
        if (d0 & D_N0) gate(0);
        if (d0 & D_N1) gate(1);
        ensure((d0 >> 16) & 1);
        bool forced = false;
        if (st & ST_INJ2) {
          st &= ~ST_INJ2;
          d2 = reg_desc(1);
          forced = true;
        } else if ((st & (ST_R0 | ST_INJ)) == ST_R0) {
          st |= ST_INJ | ST_INJ2;
          d2 = reg_desc(0);
          forced = true;
        }
        ev = D_REG | D_END | ((st & ST_CURB) ? D_B0 : D_B1) | ((st & ST_FL0) ? 0u : D_PAST0) |
             ((st & ST_FL1) ? 0u : D_PAST1) | ((st & ST_FL2) ? 0u : D_PAST2) | ((st & ST_R0) ? 0u : D_N0) |
             ((st & ST_R1) ? 0u : D_N1);
        const uint32_t act = (ss >> SS_F) | ((st & ST_R0) ? (ss >> SS_H0) : 0u) | ((st & ST_R1) ? (ss >> SS_H1) : 0u);
        if ((act & 31) || (st & ST_INJ2) || ((st & (ST_R1 | ST_REGC)) == ST_R1)) ev |= D_VALID;
        if (((st & ST_FL0) && !(st & ST_R0)) || ((st & ST_FL1) && !(st & ST_R1))) ev |= 1;
        if (!forced) d2 = grab();
      }
    } else {
      d2 = grab();
    }
    ring_step(d2);
    if (CFG_IDLE) __nanosleep(CFG_IDLE);
    if (CFG_IDLE_WAIT && (ev & 1)) __nanosleep(CFG_IDLE_WAIT);
  }
  flush(1, ring, sb + BAR_P0 + 24);
}

__device__ __forceinline__ void aux_layernorm(const uint32_t sb, const uint32_t dst, const int t, float x0, float x1,
                                              float x2, float x3) {
  float s = x0 + x1 + x2 + x3;
#pragma unroll
  for (int o = 16; o; o >>= 1) s += __shfl_xor_sync(0xffffffffu, s, o);
  if ((t & 31) == 0) stsf(sb + OFF_RED + (t >> 5) * 4, s);
  aux_sync();
  const float mean = (ldsf(sb + OFF_RED) + ldsf(sb + OFF_RED + 4) + ldsf(sb + OFF_RED + 8) + ldsf(sb + OFF_RED + 12)) *
                     (1.f / DM);
  float v = (x0 - mean) * (x0 - mean) + (x1 - mean) * (x1 - mean) + (x2 - mean) * (x2 - mean) + (x3 - mean) * (x3 - mean);
#pragma unroll
  for (int o = 16; o; o >>= 1) v += __shfl_xor_sync(0xffffffffu, v, o);
  if ((t & 31) == 0) stsf(sb + OFF_RED + 16 + (t >> 5) * 4, v);
  aux_sync();
  const float var = (ldsf(sb + OFF_RED + 16) + ldsf(sb + OFF_RED + 20) + ldsf(sb + OFF_RED + 24) + ldsf(sb + OFF_RED + 28)) *
                    (1.f / DM);
  const float m = bf16r(mean);
  const float den = bf16r(__fsqrt_rn(bf16r(bf16r(var) + 1e-5f)));
  sts32(dst + t * 8, pack_bf16(__fdividef(bf16r(x0 - m), den), __fdividef(bf16r(x1 - m), den)));
  sts32(dst + t * 8 + 4, pack_bf16(__fdividef(bf16r(x2 - m), den), __fdividef(bf16r(x3 - m), den)));
  aux_sync();
}
__device__ __forceinline__ void ldsm2t(uint32_t* r, uint32_t addr) {
  asm volatile("ldmatrix.sync.aligned.m8n8.x2.trans.shared.b16 {%0,%1}, [%2];" : "=r"(r[0]), "=r"(r[1]) : "r"(addr) : "memory");
}
__device__ __forceinline__ void mma1688(float& d0, float& d1, float& d2, float& d3, const uint32_t* a, uint32_t b0) {
  asm("mma.sync.aligned.m16n8k8.row.col.f32.bf16.bf16.f32 {%0,%1,%2,%3}, {%4,%5}, {%6}, {%0,%1,%2,%3};"
      : "+f"(d0), "+f"(d1), "+f"(d2), "+f"(d3) : "r"(a[0]), "r"(a[1]), "r"(b0));
}
__device__ __forceinline__ void cp16(uint32_t dst, const void* src) {
  asm volatile("cp.async.cg.shared.global.L2::cache_hint [%0], [%1], 16, %2;" ::"r"(dst), "l"(src), "l"(POL_FIRST) : "memory");
}
__device__ __forceinline__ void cp_wait_all() { asm volatile("cp.async.wait_all;" ::: "memory"); }
__device__ __forceinline__ void gemv_mma(float& c0, float& c1, float& c2, float& c3, uint32_t la, uint32_t astep,
                                         uint32_t xa, int nk) {
#pragma unroll 2
  for (int k = 0; k < nk; k++) {
    uint32_t a[4];
    ldsm4t(a, la);
    mma16816(c0, c1, c2, c3, a, lds32(xa), lds32(xa + 16));
    la += astep;
    xa += 32;
  }
}
__device__ __forceinline__ unsigned long long ll_raw(const unsigned long long* p) {
  unsigned long long w;
  asm volatile("ld.relaxed.gpu.global.b64 %0, [%1];" : "=l"(w) : "l"(p) : "memory");
  return w;
}
__device__ __forceinline__ bool ll_ok(unsigned long long w, uint32_t tag) { return (uint32_t)(w >> 32) == tag; }
__device__ __forceinline__ float ll_val(unsigned long long w) { return __uint_as_float((uint32_t)w); }
__device__ __forceinline__ void ll_backoff(int& it) {
  if (++it > SPIN_LIMIT) __trap();
  __nanosleep(60);
}
__device__ __forceinline__ float ll_wait1(const unsigned long long* p, uint32_t tag) {
  int it = 0;
  while (true) {
    const unsigned long long w = ll_raw(p);
    if (ll_ok(w, tag)) return ll_val(w);
    ll_backoff(it);
  }
}
__device__ __forceinline__ void ll_wait4(const unsigned long long* p, uint32_t tag, float& x0, float& x1, float& x2, float& x3) {
  int it = 0;
  while (true) {
    unsigned long long a, b, c, d;
    asm volatile("ld.relaxed.gpu.global.v2.b64 {%0,%1}, [%2];" : "=l"(a), "=l"(b) : "l"(p) : "memory");
    asm volatile("ld.relaxed.gpu.global.v2.b64 {%0,%1}, [%2];" : "=l"(c), "=l"(d) : "l"(p + 2) : "memory");
    if (ll_ok(a, tag) && ll_ok(b, tag) && ll_ok(c, tag) && ll_ok(d, tag)) {
      x0 = ll_val(a); x1 = ll_val(b); x2 = ll_val(c); x3 = ll_val(d);
      return;
    }
    ll_backoff(it);
  }
}
__device__ __forceinline__ void ll_wait4s(const unsigned long long* p, int stride, uint32_t tag, float& x0, float& x1,
                                          float& x2, float& x3) {
  unsigned long long a = ll_raw(p), b = ll_raw(p + stride), c = ll_raw(p + 2 * stride), d = ll_raw(p + 3 * stride);
  int it = 0;
  while (!(ll_ok(a, tag) && ll_ok(b, tag) && ll_ok(c, tag) && ll_ok(d, tag))) {
    ll_backoff(it);
    if (!ll_ok(a, tag)) a = ll_raw(p);
    if (!ll_ok(b, tag)) b = ll_raw(p + stride);
    if (!ll_ok(c, tag)) c = ll_raw(p + 2 * stride);
    if (!ll_ok(d, tag)) d = ll_raw(p + 3 * stride);
  }
  x0 = ll_val(a); x1 = ll_val(b); x2 = ll_val(c); x3 = ll_val(d);
}
__device__ __forceinline__ void ll_wait2s(const unsigned long long* p, int stride, uint32_t tag, float& x0, float& x1) {
  int it = 0;
  while (true) {
    const unsigned long long a = ll_raw(p), b = ll_raw(p + stride);
    if (ll_ok(a, tag) && ll_ok(b, tag)) { x0 = ll_val(a); x1 = ll_val(b); return; }
    ll_backoff(it);
  }
}
__device__ __forceinline__ void hint_arrive(unsigned int* c, const int t) {
  aux_sync();
  if (t == 0) asm volatile("red.relaxed.gpu.global.add.u32 [%0], 1;" ::"l"(c) : "memory");
}
__device__ __forceinline__ void hint_wait(const unsigned int* c, uint32_t target, const int t) {
  if (t == 0) {
    int it = 0;
    while (true) {
      uint32_t v;
      asm volatile("ld.relaxed.gpu.global.u32 %0, [%1];" : "=r"(v) : "l"(c) : "memory");
      if ((int)(v - target) >= 0) break;
      if (++it > SPIN_LIMIT) __trap();
      __nanosleep(CFG_HINT_SLEEP);
    }
  }
  aux_sync();
}
__device__ __forceinline__ void aux_qproj(const uint32_t sb, const int t, int h, int r, uint32_t xn0, uint32_t xn1, int b0,
                                          int nb, uint32_t tag) {
  const int wq = t >> 5, lane = t & 31, mat = lane >> 3, g = lane >> 2;
  const int row = (wq >> 1) * 256 + (mat >> 1) * 8 + (lane & 7), ch = 2 * (wq & 1) + (mat & 1);
  float c0 = 0.f, c1 = 0.f, c2 = 0.f, c3 = 0.f;
  gemv_mma(c0, c1, c2, c3, sb + OFF_WQ + row * 64 + ((ch ^ ((row >> 1) & 3)) << 4), 1024,
           ((g & 1) ? xn1 : xn0) + ((wq >> 1) * 256 + 2 * (lane & 3)) * 2, 16);
  if ((lane & 3) == 0) {
    const uint32_t e = sb + SC_RED4 + ((wq >> 1) * 64 + (wq & 1) * 16 + g) * 4;
    stsf(e, c0); stsf(e + 32, c2); stsf(e + 128, c1); stsf(e + 160, c3);
  }
  aux_sync();
  if (t < 32 * nb)
    ll_st(&g_Q[b0 + (t >> 5)][h][r * 32 + (t & 31)], bf16r(ldsf(sb + SC_RED4 + t * 4) + ldsf(sb + SC_RED4 + (64 + t) * 4)), tag);
  aux_sync();
  if (t < nb) asm volatile("red.relaxed.gpu.global.add.u32 [%0], 1;" ::"l"(&g_cntQ[b0 + t][h]) : "memory");
}
__device__ __forceinline__ void qfrag_store(uint32_t qf, const int t, float q) {
  const int half = t >> 6, j = (t >> 4) & 3, k = t & 15;
  const uint32_t off = (j >> 1) * 128 + (half * 4 + ((k & 7) >> 1)) * 16 + ((j & 1) * 2 + (k >> 3)) * 4 + (k & 1) * 2;
  sts16(qf + off, (uint16_t)(__float_as_uint(q) >> 16));
}

__device__ __forceinline__ void aux_chain(const Params& p, const uint32_t sb, const int t, const int c, const int b,
                                          const int layer, const uint32_t epoch, uint32_t area, uint32_t astride,
                                          uint32_t pbar, float& xres) {
  const uint32_t tag = epoch * 4 + 1 + layer;
  const uint32_t use = 2 * (epoch - 1) + layer + 1;
  const int h = c >> 2, r = c & 3, wq = t >> 5, lane = t & 31, mat = lane >> 3, g = lane >> 2, i8 = lane & 7;
  const int nsrc = p.ht ? 5 : 4;
  if (t == 0) stamp2(b + 2 * layer, 0);
  mbar_wait(pbar, 0);
  if (t == 0) stamp(2 + 2 * (b + 2 * layer));
  {
    float M = -INFINITY;
#pragma unroll 1
    for (int k = 0; k < 8; k++) M = fmaxf(M, ldsf(area + k * astride + 512));
    float O = 0.f, L = 0.f;
#pragma unroll 1
    for (int k = 0; k < 8; k++) {
      const float sc = ex2(ldsf(area + k * astride + 512) - M);
      O = fmaf(sc, ldsf(area + k * astride + t * 4), O);
      L = fmaf(sc, ldsf(area + k * astride + 516), L);
    }
    ll_st(&g_P[b][h][r][t], O, tag);
    if (t == 0) { ll_st(&g_P[b][h][r][128], M, tag); ll_st(&g_P[b][h][r][129], L, tag); }
  }
  hint_arrive(&g_cntP[b][h], t);
  hint_wait(&g_cntP[b][h], use * nsrc, t);
  if (t == 0) stamp2(b + 2 * layer, 1);
  {
    const int sl = lane < nsrc ? lane : 0;
    const unsigned long long* P0 = &g_P[b][h][0][t];
    unsigned long long wm, wl, w0, w1, w2, w3, w4;
    int it = 0;
    while (true) {
      wm = ll_raw(&g_P[b][h][sl][128]); wl = ll_raw(&g_P[b][h][sl][129]);
      w0 = ll_raw(P0); w1 = ll_raw(P0 + 132); w2 = ll_raw(P0 + 264); w3 = ll_raw(P0 + 396);
      w4 = ll_raw(P0 + (nsrc == 5 ? 528 : 0));
      const bool ok = ll_ok(wm, tag) && ll_ok(wl, tag) && ll_ok(w0, tag) && ll_ok(w1, tag) && ll_ok(w2, tag) &&
                      ll_ok(w3, tag) && ll_ok(w4, tag);
      if (__all_sync(0xffffffffu, ok)) break;
      ll_backoff(it);
    }
    const float ms = lane < nsrc ? ll_val(wm) : -INFINITY;
    float M = ms;
#pragma unroll
    for (int o = 4; o; o >>= 1) M = fmaxf(M, __shfl_xor_sync(0xffffffffu, M, o));
    M = __shfl_sync(0xffffffffu, M, 0);
    const float e = (lane < nsrc) ? ex2(ms - M) : 0.f;
    float L = e * ll_val(wl);
#pragma unroll
    for (int o = 4; o; o >>= 1) L += __shfl_xor_sync(0xffffffffu, L, o);
    L = __shfl_sync(0xffffffffu, L, 0);
    const float wgt = __fdividef(e, L);
    float o = __shfl_sync(0xffffffffu, wgt, 0) * ll_val(w0);
    o = fmaf(__shfl_sync(0xffffffffu, wgt, 1), ll_val(w1), o);
    o = fmaf(__shfl_sync(0xffffffffu, wgt, 2), ll_val(w2), o);
    o = fmaf(__shfl_sync(0xffffffffu, wgt, 3), ll_val(w3), o);
    o = fmaf(__shfl_sync(0xffffffffu, wgt, 4), ll_val(w4), o);
    sts16(sb + SC_O + t * 2, (uint16_t)(pack_bf16(o, 0.f) & 0xffffu));
  }
  aux_sync();
  if (t == 0) stamp2(b + 2 * layer, 2);
#pragma unroll 1
  for (int m = 0; m < 2; m++) {
    const int mt = 2 * wq + m;
    float c0 = 0.f, c1 = 0.f, c2 = 0.f, c3 = 0.f;
    gemv_mma(c0, c1, c2, c3, sb + OFF_WO + ((mat >> 1) * 8 + i8) * 256 + (((2 * mt + (mat & 1)) ^ i8) << 4), 4096,
             sb + SC_O + (lane & 3) * 4, 8);
    if ((lane & 3) < 2) ll_st(&g_Z[b][h][r * 128 + mt * 16 + g + 8 * (lane & 1)], (lane & 1) ? c2 : c0, tag);
  }
  hint_arrive(&g_cntZ[b][r], t);
  if (t == 0) stamp2(b + 2 * layer, 3);
  hint_wait(&g_cntZ[b][c >> 5], use * NH, t);
  {
    const int col = 4 * c + wq;
    float z = ll_wait1(&g_Z[b][lane][col], tag);
    __syncwarp();
#pragma unroll
    for (int o = 16; o; o >>= 1) z += __shfl_xor_sync(0xffffffffu, z, o);
    xres = bf16r(xres + bf16r(z));
    if (lane == 0) ll_st(&g_X1[b][col], xres, tag);
    hint_arrive(&g_cntX1[b], t);
  }
  if (t == 0) stamp2(b + 2 * layer, 4);
  const int ng = c < NGRP2 ? 2 : 1;
  {
    float x0, x1, x2, x3;
    hint_wait(&g_cntX1[b], use * NMAIN, t);
    ll_wait4(&g_X1[b][4 * t], tag, x0, x1, x2, x3);
    if (t == 0) stamp2(b + 2 * layer, 5);
    aux_layernorm(sb, sb + OFF_XN, t, x0, x1, x2, x3);
  }
#pragma unroll 1
  for (int gi = 0; gi < ng; gi++) {
    float c0 = 0.f, c1 = 0.f, c2 = 0.f, c3 = 0.f;
    gemv_mma(c0, c1, c2, c3, sb + OFF_WF + gi * WF_BYTES + (mat & 1) * 8192 + (wq * 128 + (mat >> 1) * 8 + i8) * 16, 256,
             sb + OFF_XN + (wq * 128 + 2 * (lane & 3)) * 2, 8);
    if ((lane & 3) == 0) {
      const uint32_t e = sb + SC_RED4 + ((gi * 4 + wq) * 16 + g) * 4;
      stsf(e, c0); stsf(e + 32, c2);
    }
  }
  aux_sync();
  if (t < 8 * ng) {
    const uint32_t e = sb + SC_RED4 + ((t >> 3) * 64 + (t & 7)) * 4;
    const float gt = ldsf(e) + ldsf(e + 64) + ldsf(e + 128) + ldsf(e + 192);
    const float up = ldsf(e + 32) + ldsf(e + 96) + ldsf(e + 160) + ldsf(e + 224);
    sts16(sb + SC_H + t * 2, (uint16_t)(pack_bf16(bf16r(gt) * bf16r(up), 0.f) & 0xffffu));
  }
  aux_sync();
  if (t == 0) stamp2(b + 2 * layer, 6);
#pragma unroll 1
  for (int m = 0; m < 8; m++) {
    const int mt = 8 * wq + m;
    float c0 = 0.f, c1 = 0.f, c2 = 0.f, c3 = 0.f;
    for (int gi = 0; gi < ng; gi++) {
      uint32_t a[2];
      ldsm2t(a, sb + OFF_WF + gi * WF_BYTES + 16384 + i8 * 1024 + (((2 * mt + (mat & 1)) ^ i8) << 4));
      mma1688(c0, c1, c2, c3, a, lds32(sb + SC_H + gi * 16 + (lane & 3) * 4));
    }
    if ((lane & 3) < 2) ll_st(&g_D[b][c][mt * 16 + g + 8 * (lane & 1)], (lane & 1) ? c2 : c0, tag);
  }
  hint_arrive(&g_cntD[b], t);
  if (t == 0) stamp2(b + 2 * layer, 7);
  hint_wait(&g_cntD[b], use * NMAIN, t);
  {
    const int col = 4 * c + wq;
    float d0, d1, d2, d3;
    ll_wait4s(&g_D[b][lane][col], 32 * DM, tag, d0, d1, d2, d3);
    float d = (d0 + d1) + (d2 + d3);
    __syncwarp();
#pragma unroll
    for (int o = 16; o; o >>= 1) d += __shfl_xor_sync(0xffffffffu, d, o);
    xres = bf16r(xres + bf16r(d));
    if (lane == 0) {
      if (layer == 0) ll_st(&g_X2[b][col], xres, tag);
      else p.out[b * DM + col] = __float2bfloat16_rn(xres);
    }
    if (layer == 0) hint_arrive(&g_cntX2[b], t);
  }
  if (t == 0) stamp2(b + 2 * layer, 8);
  if (layer == 0) {
    {
      float x0, x1, x2, x3;
      hint_wait(&g_cntX2[b], epoch * NMAIN, t);
      ll_wait4(&g_X2[b][4 * t], tag, x0, x1, x2, x3);
      if (t == 0) stamp2(b + 2 * layer, 9);
      aux_layernorm(sb, sb + OFF_XN, t, x0, x1, x2, x3);
    }
    aux_qproj(sb, t, h, r, sb + OFF_XN, sb + OFF_XN, b, 1, tag);
    if (t == 0) stamp2(b + 2 * layer, 10);
    hint_wait(&g_cntQ[b][h], epoch * 8, t);
    qfrag_store(sb + OFF_QF + b * 256, t, ll_wait1(&g_Q[b][h][t], tag));
    aux_sync();
    if (t == 0) mbar_arrive(sb + (b ? BAR_R1 : BAR_R0));
  }
}

__device__ __forceinline__ void aux_fill_wq(const Params& p, const uint32_t sb, const int t, const int c) {
  const int h = c >> 2, r = c & 3;
#pragma unroll 4
  for (int i = 0; i < 16; i++) {
    const int row = i * 32 + (t >> 2), ch = t & 3;
    cp16(sb + OFF_WQ + row * 64 + ((ch ^ ((row >> 1) & 3)) << 4), p.wq + (size_t)row * (NH * 128) + h * 128 + r * 32 + ch * 8);
  }
}
__device__ __forceinline__ void aux_fill_rest(const Params& p, const uint32_t sb, const int t, const int c) {
  const int h = c >> 2, r = c & 3;
#pragma unroll 1
  for (int i = 0; i < 16; i++) {
    const int row = i * 8 + (t >> 4), ch = t & 15;
    cp16(sb + OFF_WO + row * 256 + ((ch ^ (row & 7)) << 4), p.wo + (size_t)(h * 128 + row) * DM + r * 128 + ch * 8);
    if ((i & 3) == 3) cp_wait_all();
  }
  const int ng = c < NGRP2 ? 2 : 1;
#pragma unroll 1
  for (int gi = 0; gi < ng; gi++) {
    const int G = gi ? NMAIN + c : c;
    const uint32_t base = sb + OFF_WF + gi * WF_BYTES;
#pragma unroll 1
    for (int i = 0; i < 4; i++) {
      const int q = i * 128 + t;
      cp16(base + q * 16, p.wg + (size_t)q * FF + G * 8);
      cp16(base + 8192 + q * 16, p.wu + (size_t)q * FF + G * 8);
      const int row = q >> 6, ch = q & 63;
      cp16(base + 16384 + row * 1024 + ((ch ^ row) << 4), p.wd + (size_t)(G * 8 + row) * DM + ch * 8);
      if (i & 1) cp_wait_all();
    }
  }
  aux_sync();
}

__device__ __forceinline__ void aux_init_main(const Params& p, const uint32_t sb, const int t, const int c, const uint32_t tag) {
  const uint2 xa = *reinterpret_cast<const uint2*>(p.x + 4 * t);
  const uint2 xb = *reinterpret_cast<const uint2*>(p.x + DM + 4 * t);
  if (t == 0) stamp2(0, 14);
  aux_layernorm(sb, sb + OFF_XN, t, bflo(xa.x), bfhi(xa.x), bflo(xa.y), bfhi(xa.y));
  aux_layernorm(sb, sb + SC_XN1, t, bflo(xb.x), bfhi(xb.x), bflo(xb.y), bfhi(xb.y));
  cp_wait_all();
  aux_sync();
  if (t == 0) stamp2(1, 14);
  aux_qproj(sb, t, c >> 2, c & 3, sb + OFF_XN, sb + SC_XN1, 0, 2, tag);
  if (t == 0) stamp2(2, 14);
}

__device__ __forceinline__ void aux_main(const Params& p, const uint32_t sb, const int t, const int c, const uint32_t epoch) {
  const int h = c >> 2;
  const uint32_t tag0 = epoch * 4;
  {
    float q0, q1;
    ll_wait2s(&g_Q[0][h][t], NH * 128, tag0, q0, q1);
    qfrag_store(sb + OFF_QF, t, q0);
    qfrag_store(sb + OFF_QF + 256, t, q1);
  }
  aux_sync();
  if (t == 0) mbar_arrive(sb + BAR_Q1);
  if (t == 0) stamp(1);
  aux_fill_rest(p, sb, t, c);
  float xres0, xres1;
  {
    const int col = 4 * c + (t >> 5);
    xres0 = __bfloat162float(p.x[col]);
    xres1 = __bfloat162float(p.x[DM + col]);
  }
#pragma unroll 1
  for (int k = 0; k < 4; k++) {
    const int b = k & 1, layer = k >> 1;
    float xr = b ? xres1 : xres0;
    aux_chain(p, sb, t, c, b, layer, epoch, k == 3 ? sb + OFF_RING : sb + OFF_PART, k == 3 ? RING_W : 528,
              sb + BAR_P0 + 8 * k, xr);
    if (b) xres1 = xr; else xres0 = xr;
    if (t == 0) stamp(3 + 2 * k);
  }
}

__device__ __forceinline__ void aux_helper(const uint32_t sb, const int t, const int j, const uint32_t epoch) {
  const uint32_t tag0 = epoch * 4, tag1 = tag0 + 1, tag2 = tag0 + 2;
  const uint32_t qf = sb + OFF_QF_HELP;
#pragma unroll 1
  for (int w = 0; w < 8; w++) {
    hint_wait(&g_cntQ[1][8 * j + w], epoch * 8 - 4, t);
    for (int b = 0; b < 2; b++) qfrag_store(qf + w * 512 + b * 256, t, ll_wait1(&g_Q[b][8 * j + w][t], tag0));
  }
  aux_sync();
  if (t == 0) mbar_arrive(sb + BAR_Q1);
#pragma unroll 1
  for (int k = 0; k < 4; k++) {
    const int b = k & 1, layer = k >> 1;
    const uint32_t tag = layer ? tag2 : tag1;
    const uint32_t area = k == 3 ? sb + OFF_RING : sb + OFF_PART, astride = k == 3 ? RING_W : 528;
    mbar_wait(sb + BAR_P0 + 8 * k, 0);
    for (int w = 0; w < 8; w++) {
      ll_st(&g_P[b][8 * j + w][4][t], ldsf(area + w * astride + t * 4), tag);
      if (t < 2) ll_st(&g_P[b][8 * j + w][4][128 + t], ldsf(area + w * astride + 512 + t * 4), tag);
    }
    aux_sync();
    if (t < 8) asm volatile("red.relaxed.gpu.global.add.u32 [%0], 1;" ::"l"(&g_cntP[b][8 * j + t]) : "memory");
    if (layer == 0) {
#pragma unroll 1
      for (int w = 0; w < 8; w++) {
        hint_wait(&g_cntQ[b][8 * j + w], epoch * 8, t);
        qfrag_store(qf + w * 512 + b * 256, t, ll_wait1(&g_Q[b][8 * j + w][t], tag1));
      }
      aux_sync();
      if (t == 0) mbar_arrive(sb + (b ? BAR_R1 : BAR_R0));
    }
  }
}

__global__ void __launch_bounds__(384, 1)
fused_decode_kernel(const __grid_constant__ CUtensorMap tmK, const __grid_constant__ CUtensorMap tmV,
                    const __grid_constant__ Params p) {
  extern __shared__ __align__(1024) uint8_t smem[];
  const uint32_t sb = (uint32_t)__cvta_generic_to_shared(smem);
  const int tid = threadIdx.x;
  const int w = __shfl_sync(0xffffffffu, tid >> 5, 0);
  const int lane = tid & 31;
  const int c = blockIdx.x;
  const bool helper = c >= NMAIN;

  const uint32_t side = sb + (helper ? OFF_W + 4096 : OFF_WF + (c < NGRP2 ? 2 : 1) * WF_BYTES);
  if (w < 8) {
    if (lane == 0) {
      const int nt = (TPH - p.ht) >> 2;
      uint32_t base, dyn, n, q, ctr, qf, st0, pk, rt;
      if (!helper) {
        const uint32_t ns = (sb + SMEM_BYTES - side) >> 12;
        base = (c >> 2) * TPH + (c & 3) * nt;
        rt = base + w * RP;
        st0 = base + 8 * RP + w;
        pk = w | (8u << 8) | (8u << 16) | (((ns - w + 7) >> 3) << 24);
        dyn = base + 8 * RP + ns;
        n = nt - 8 * RP - ns;
        q = p.q;
        ctr = sb + OFF_CTR;
        qf = sb + OFF_QF;
      } else {
        base = ((c - NMAIN) * 8 + w) * TPH + (TPH - p.ht);
        rt = base;
        st0 = base + RP;
        pk = (w * S_HELP_W) | (1u << 8) | (1u << 16) | ((uint32_t)S_HELP_W << 24);
        dyn = base + RP + S_HELP_W;
        n = p.ht - RP - S_HELP_W;
        q = p.q >> 3;
        ctr = sb + OFF_CTR + w * 4;
        qf = sb + OFF_QF_HELP + w * 512;
      }
      const uint32_t wp = sb + OFF_WP + w * 32;
      const uint32_t seg = helper ? side + 8 * S_HELP_W * 4096 + w * 128 : sb + OFF_SEG;
      sts32(wp, seg);
      sts32(wp + 16, qf); sts32(wp + 20, st0); sts32(wp + 24, pk); sts32(wp + 28, rt);
      if (helper || w == 0) {
        const uint32_t pl = n - q;
        auto blk = [&](int i, uint32_t lim, uint32_t base_d, uint32_t pf, uint32_t cnt) {
          sts32(seg + i * 16, lim); sts32(seg + i * 16 + 4, base_d); sts32(seg + i * 16 + 8, pf); sts32(seg + i * 16 + 12, cnt);
        };
        blk(0, n, D_VALID | D_B0 | dyn, pl, ctr);
        blk(1, 2 * n, (D_VALID | D_B1 | D_PAST0) + dyn + TPB - n, n + pl, ctr);
        blk(2, 2 * n + pl, (D_VALID | D_B0 | D_N0 | D_PAST0 | D_PAST1) + dyn - 2 * n, 0xffffffffu, ctr);
        blk(3, 2 * n + 2 * pl, (D_VALID | D_B1 | D_N1 | D_PASTS) + dyn + TPB - 2 * n - pl, 0xffffffffu, ctr);
        blk(4, 0, 0, 0xffffffffu, ctr);
        blk(5, q, dyn + n - 1, 0, ctr + 32);
      }
      for (int s = 0; s < 4; s++) mbar_init(sb + OFF_RBAR + (w * 4 + s) * 8, 1);
      for (int s = w; s < 40; s += 8) mbar_init(sb + OFF_SBAR + s * 8, 1);
    }
  } else {
    if (!helper) aux_fill_wq(p, sb, tid - 256, c);
    if (w == 8) {
      if (lane < 24) sts32(sb + OFF_CTR + lane * 4, 0);
      if (lane == 0) {
        mbar_init(sb + BAR_Q1, 1); mbar_init(sb + BAR_R0, 1); mbar_init(sb + BAR_R1, 1);
        for (int k = 0; k < 4; k++) mbar_init(sb + BAR_P0 + 8 * k, 8);
      }
    }
  }
  asm volatile("fence.mbarrier_init.release.cluster;" ::: "memory");
  asm volatile("fence.proxy.async.shared::cta;" ::: "memory");
  __syncthreads();
  if (tid == 0) stamp(0);

  if (w < 8) {
    stream_prologue(&tmK, &tmV, sb, side, w, lane);
    asm volatile("setmaxnreg.inc.sync.aligned.u32 %0;" ::"n"(CFG_REG_S));
    int lane2;
    asm volatile("mov.u32 %0, %%laneid;" : "=r"(lane2));
    stream_warp(&tmK, &tmV, sb, side, w, lane2, p.zero);
    if (lane2 == 0 && w == 0) stamp(12);
  } else {
    uint32_t epoch;
    asm volatile("ld.relaxed.gpu.global.u32 %0, [%1];" : "=r"(epoch) : "l"(&g_epoch) : "memory");
    epoch += 1;
    if (!helper) aux_init_main(p, sb, tid - 256, c, epoch * 4);
    asm volatile("setmaxnreg.dec.sync.aligned.u32 %0;" ::"n"(CFG_REG_A));
    int t;
    asm volatile("mov.u32 %0, %%tid.x;" : "=r"(t));
    t -= 256;
    if (!helper) aux_main(p, sb, t, c, epoch);
    else aux_helper(sb, t, c - NMAIN, epoch);
    if (c == 0 && t == 0) asm volatile("st.relaxed.gpu.global.u32 [%0], %1;" ::"l"(&g_epoch), "r"(epoch) : "memory");
    if (t == 0) stamp(13);
  }
}

typedef CUresult (*EncodeTiledFn)(CUtensorMap*, CUtensorMapDataType, cuuint32_t, void*, const cuuint64_t*,
                                  const cuuint64_t*, const cuuint32_t*, const cuuint32_t*, CUtensorMapInterleave,
                                  CUtensorMapSwizzle, CUtensorMapL2promotion, CUtensorMapFloatOOBfill);

}

extern "C" void kernel_launch(void* const* d_in, const int* in_sizes, int n_in, void* d_out, int out_size) {
  (void)in_sizes; (void)n_in; (void)out_size;
  static EncodeTiledFn encode = nullptr;
  static int sms = 0;
  if (!encode) {
    void* fn = nullptr;
    cudaDriverEntryPointQueryResult qr;
    cudaGetDriverEntryPoint("cuTensorMapEncodeTiled", &fn, cudaEnableDefault, &qr);
    encode = (EncodeTiledFn)fn;
    int dev = 0;
    cudaGetDevice(&dev);
    cudaDeviceGetAttribute(&sms, cudaDevAttrMultiProcessorCount, dev);
    cudaFuncSetAttribute(fused_decode_kernel, cudaFuncAttributeMaxDynamicSharedMemorySize, SMEM_BYTES);
  }
  CUtensorMap tmK, tmV;
  const cuuint64_t gdim[2] = {64, (cuuint64_t)2 * NH * SK * 2};
  const cuuint64_t gstr[1] = {128};
  const cuuint32_t box[2] = {64, 16};
  const cuuint32_t estr[2] = {1, 1};
  encode(&tmK, CU_TENSOR_MAP_DATA_TYPE_BFLOAT16, 2, d_in[1], gdim, gstr, box, estr, CU_TENSOR_MAP_INTERLEAVE_NONE,
         CU_TENSOR_MAP_SWIZZLE_128B, CU_TENSOR_MAP_L2_PROMOTION_NONE, CU_TENSOR_MAP_FLOAT_OOB_FILL_NONE);
  encode(&tmV, CU_TENSOR_MAP_DATA_TYPE_BFLOAT16, 2, d_in[2], gdim, gstr, box, estr, CU_TENSOR_MAP_INTERLEAVE_NONE,
         CU_TENSOR_MAP_SWIZZLE_128B, CU_TENSOR_MAP_L2_PROMOTION_NONE, CU_TENSOR_MAP_FLOAT_OOB_FILL_NONE);
  Params p;
  p.x = (const __nv_bfloat16*)d_in[0];
  p.wq = (const __nv_bfloat16*)d_in[3];
  p.wo = (const __nv_bfloat16*)d_in[4];
  p.wg = (const __nv_bfloat16*)d_in[6];
  p.wu = (const __nv_bfloat16*)d_in[7];
  p.wd = (const __nv_bfloat16*)d_in[8];
  p.out = (__nv_bfloat16*)d_out;
  const bool helpers = sms >= NMAIN + NHELP;
  p.ht = helpers ? CFG_HT : 0;
  p.q = CFG_Q;
  p.zero = 0;
  fused_decode_kernel<<<helpers ? NMAIN + NHELP : NMAIN, 384, SMEM_BYTES, cudaStreamPerThread>>>(tmK, tmV, p);
}
```

```cpp
#include <cuda_runtime.h>
#include <cuda_bf16.h>
#include <cuda.h>
#include <stdint.h>

namespace {

constexpr int DM = 512;
constexpr int NH = 32;
constexpr int SK = 16384;
constexpr int FF = 1376;
constexpr int TPH = SK / 8;
constexpr int TPB = NH * TPH;

#define CFG_RP 6
#define CFG_REG_S 232
#define CFG_REG_A 40
#define CFG_Q 144
#define CFG_IDLE 0
#define CFG_IDLE_WAIT 0
#define CFG_HINT_SLEEP 20
#define CFG_PFDELAY 0
#define CFG_RING_PRIO 0
#define CFG_SIDE_EVERY 1
#define CFG_HINT_K 4
#define CFG_SLOTS 3
#define CFG_SIDE_MAX 1
#define CFG_H2 30
#define CFG_HT 56
constexpr int RP = CFG_RP;
constexpr int NMAIN = 128;
constexpr int NHELP = 4;
constexpr int S_HELP_W = CFG_SLOTS == 3 ? 5 : 4;
constexpr int NGRP = FF / 8;
static_assert(NGRP - NMAIN == NH + 12, "second ffn groups: quarter 0 of every head, quarter 1 of the first 12 heads");
__host__ __device__ constexpr int ffn_groups(int c) { return ((c & 3) == 0 || ((c & 3) == 1 && (c >> 2) < 12)) ? 2 : 1; }
__host__ __device__ constexpr int ffn_second(int c) { return NMAIN + (c >> 2) + ((c & 3) ? NH : 0); }

constexpr uint32_t SMEM_BYTES = 232448;
constexpr uint32_t OFF_RING = 0;
constexpr uint32_t RING_W = CFG_SLOTS * 2048;
constexpr uint32_t OFF_MISC = 8 * RING_W;
constexpr uint32_t OFF_RBAR = OFF_MISC;
constexpr uint32_t OFF_SBAR = OFF_RBAR + 32 * 8;
constexpr uint32_t OFF_CBAR = OFF_SBAR + 40 * 8;
constexpr uint32_t BAR_Q1 = OFF_CBAR + 0, BAR_R0 = OFF_CBAR + 8, BAR_R1 = OFF_CBAR + 16;
constexpr uint32_t BAR_P0 = OFF_CBAR + 24;
constexpr uint32_t OFF_CTR = OFF_CBAR + 56;
constexpr uint32_t OFF_HELD = OFF_CTR + 96;
constexpr uint32_t OFF_WP = OFF_MISC + 768;
constexpr uint32_t OFF_QF = OFF_WP + 256;
constexpr uint32_t OFF_PART = OFF_QF + 512;
constexpr uint32_t OFF_XN = OFF_PART + 8 * 132 * 4;
constexpr uint32_t OFF_RED = OFF_XN + 1024;
constexpr uint32_t OFF_XRES = OFF_RED + 32;
constexpr uint32_t OFF_SEG = OFF_RED + 64;
constexpr uint32_t OFF_W = OFF_MISC + 7168;
constexpr uint32_t OFF_WQ = OFF_W;
constexpr uint32_t OFF_WO = OFF_WQ + 32768;
constexpr uint32_t OFF_WF = OFF_WO + 32768;
constexpr uint32_t WF_BYTES = 24576;
constexpr uint32_t OFF_QF_HELP = OFF_W;
static_assert(OFF_HELD + 32 <= OFF_WP, "smem map");
static_assert(OFF_SEG + 128 <= OFF_W && OFF_W % 1024 == 0 && OFF_WF % 1024 == 0, "smem map");
constexpr uint32_t SC_RED4 = OFF_PART;
constexpr uint32_t SC_XN1 = OFF_PART + 1024;
constexpr uint32_t SC_O = OFF_PART + 2048;
constexpr uint32_t SC_H = OFF_PART + 2560;

__device__ __align__(16) uint32_t g_P[2][NH][5][132];
__device__ __align__(16) uint32_t g_Z[2][NH][DM];
__device__ __align__(16) uint32_t g_X1[2][DM];
__device__ __align__(16) uint32_t g_D[2][NMAIN][DM];
__device__ __align__(16) uint32_t g_X2[2][DM];
__device__ __align__(16) uint32_t g_Q[2][NH][128];
__device__ unsigned int g_epoch;
__device__ unsigned int g_cntP[2][NH], g_cntQ[2][NH], g_cntZ[2][4], g_cntX1[2], g_cntD[2], g_cntX2[2];

struct Params {
  const __nv_bfloat16* x;
  const __nv_bfloat16* wq;
  const __nv_bfloat16* wo;
  const __nv_bfloat16* wg;
  const __nv_bfloat16* wu;
  const __nv_bfloat16* wd;
  __nv_bfloat16* out;
  int ht;
  int h2;
  int q;
  uint32_t zero;
  const uint8_t* kbytes;
  const uint8_t* vbytes;
};

constexpr uint32_t D_TILE = 0x1FFFFu;
constexpr uint32_t D_B0 = 1u << 17, D_B1 = 1u << 18;
constexpr uint32_t D_N0 = 1u << 19, D_N1 = 1u << 20;
constexpr uint32_t D_PF = 1u << 21;
constexpr uint32_t D_REG = 1u << 22;
constexpr uint32_t D_PAST0 = 1u << 23, D_PAST1 = 1u << 24, D_PAST2 = 1u << 25;
constexpr uint32_t D_VALID = 1u << 26, D_END = 1u << 27;
constexpr uint32_t D_PASTS = D_PAST0 | D_PAST1 | D_PAST2;
constexpr uint32_t ST_R0 = 1u << 0, ST_R1 = 1u << 1, ST_INJ = 1u << 2, ST_INJ2 = 1u << 3, ST_FL0 = 1u << 7,
                   ST_FL1 = 1u << 8, ST_FL2 = 1u << 9, ST_REGC = 1u << 10, ST_CURB = 1u << 11,
                   ST_SONLY = 1u << 12;
constexpr int SH_SKIP = 13;
constexpr int SS_F = 0, SS_H0 = 5, SS_H1 = 10, SS_B = 15, SS_K = 20, SS_P = 25;

constexpr uint64_t POL_FIRST = 0x12F0000000000000ull;
constexpr uint64_t POL_NORMAL = 0x16F0000000000000ull;
constexpr float SCALE_LOG2 = 0.08838834764831845f * 1.4426950408889634f;
constexpr int SPIN_LIMIT = 1 << 22;

__device__ __forceinline__ void mbar_init(uint32_t bar, uint32_t cnt) {
  asm volatile("mbarrier.init.shared::cta.b64 [%0], %1;" ::"r"(bar), "r"(cnt) : "memory");
}
__device__ __forceinline__ void mbar_expect_tx(uint32_t bar, uint32_t bytes) {
  asm volatile("mbarrier.arrive.expect_tx.shared::cta.b64 _, [%0], %1;" ::"r"(bar), "r"(bytes) : "memory");
}
__device__ __forceinline__ void mbar_arrive(uint32_t bar) {
  asm volatile("mbarrier.arrive.shared::cta.b64 _, [%0];" ::"r"(bar) : "memory");
}
__device__ __forceinline__ bool mbar_test(uint32_t bar, uint32_t parity) {
  uint32_t ok;
  asm volatile("{\n.reg .pred p;\nmbarrier.test_wait.parity.shared::cta.b64 p, [%1], %2;\nselp.u32 %0, 1, 0, p;\n}"
               : "=r"(ok) : "r"(bar), "r"(parity) : "memory");
  return ok != 0;
}
__device__ __forceinline__ bool mbar_try(uint32_t bar, uint32_t parity) {
  uint32_t ok;
  asm volatile("{\n.reg .pred p;\nmbarrier.try_wait.parity.shared::cta.b64 p, [%1], %2;\nselp.u32 %0, 1, 0, p;\n}"
               : "=r"(ok) : "r"(bar), "r"(parity) : "memory");
  return ok != 0;
}
__device__ __forceinline__ void mbar_wait(uint32_t bar, uint32_t parity) {
  int it = 0;
  while (!__all_sync(0xffffffffu, mbar_try(bar, parity)))
    if (++it > SPIN_LIMIT) __trap();
}
__device__ __forceinline__ void tma_load(uint32_t dst, const CUtensorMap* tm, int c0, int row, uint32_t bar) {
  asm volatile(
      "cp.async.bulk.tensor.2d.shared::cluster.global.tile.mbarrier::complete_tx::bytes.L2::cache_hint"
      " [%0], [%1, {%2, %3}], [%4], %5;" ::"r"(dst), "l"(tm), "r"(c0), "r"(row), "r"(bar), "l"(POL_FIRST)
      : "memory");
}
__device__ __forceinline__ void ldsm4(uint32_t* r, uint32_t addr) {
  asm volatile("ldmatrix.sync.aligned.m8n8.x4.shared.b16 {%0,%1,%2,%3}, [%4];"
               : "=r"(r[0]), "=r"(r[1]), "=r"(r[2]), "=r"(r[3]) : "r"(addr) : "memory");
}
__device__ __forceinline__ void ldsm4t(uint32_t* r, uint32_t addr) {
  asm volatile("ldmatrix.sync.aligned.m8n8.x4.trans.shared.b16 {%0,%1,%2,%3}, [%4];"
               : "=r"(r[0]), "=r"(r[1]), "=r"(r[2]), "=r"(r[3]) : "r"(addr) : "memory");
}
__device__ __forceinline__ void mma16816(float& d0, float& d1, float& d2, float& d3, const uint32_t* a, uint32_t b0,
                                         uint32_t b1) {
  asm("mma.sync.aligned.m16n8k16.row.col.f32.bf16.bf16.f32 {%0,%1,%2,%3}, {%4,%5,%6,%7}, {%8,%9}, {%0,%1,%2,%3};"
      : "+f"(d0), "+f"(d1), "+f"(d2), "+f"(d3)
      : "r"(a[0]), "r"(a[1]), "r"(a[2]), "r"(a[3]), "r"(b0), "r"(b1));
}
__device__ __forceinline__ void mma16816v(float& d0, float& d1, float& d2, float& d3, const uint32_t* a, uint32_t b0,
                                          uint32_t b1) {
  asm volatile("mma.sync.aligned.m16n8k16.row.col.f32.bf16.bf16.f32 {%0,%1,%2,%3}, {%4,%5,%6,%7}, {%8,%9}, {%0,%1,%2,%3};"
               : "+f"(d0), "+f"(d1), "+f"(d2), "+f"(d3)
               : "r"(a[0]), "r"(a[1]), "r"(a[2]), "r"(a[3]), "r"(b0), "r"(b1));
}
__device__ __forceinline__ uint32_t lds32(uint32_t a) {
  uint32_t v;
  asm volatile("ld.shared.u32 %0, [%1];" : "=r"(v) : "r"(a) : "memory");
  return v;
}
__device__ __forceinline__ uint4 lds128(uint32_t a) {
  uint4 v;
  asm volatile("ld.shared.v4.u32 {%0,%1,%2,%3}, [%4];" : "=r"(v.x), "=r"(v.y), "=r"(v.z), "=r"(v.w) : "r"(a) : "memory");
  return v;
}
__device__ __forceinline__ float ldsf(uint32_t a) {
  float v;
  asm volatile("ld.shared.f32 %0, [%1];" : "=f"(v) : "r"(a) : "memory");
  return v;
}
__device__ __forceinline__ void stsf(uint32_t a, float v) {
  asm volatile("st.shared.f32 [%0], %1;" ::"r"(a), "f"(v) : "memory");
}
__device__ __forceinline__ void sts32(uint32_t a, uint32_t v) {
  asm volatile("st.shared.u32 [%0], %1;" ::"r"(a), "r"(v) : "memory");
}
__device__ __forceinline__ void sts16(uint32_t a, uint16_t v) {
  asm volatile("st.shared.u16 [%0], %1;" ::"r"(a), "h"(v) : "memory");
}
__device__ __forceinline__ float ex2(float x) {
  float y;
  asm("ex2.approx.ftz.f32 %0, %1;" : "=f"(y) : "f"(x));
  return y;
}
__device__ __forceinline__ int dep_zero(uint32_t r, uint32_t zero) { return (int)(r & zero); }
__device__ __forceinline__ void tma_issue(uint32_t dst, const CUtensorMap* tm, int c0, int row, uint32_t bar) {
  asm volatile(
      "{\n.reg .pred P;\nelect.sync _|P, 0xffffffff;\n"
      "@P mbarrier.arrive.expect_tx.shared::cta.b64 _, [%4], 2048;\n"
      "@P cp.async.bulk.tensor.2d.shared::cluster.global.tile.mbarrier::complete_tx::bytes.L2::cache_hint"
      " [%0], [%1, {%2, %3}], [%4], %5;\n}" ::"r"(dst), "l"(tm), "r"(c0), "r"(row), "r"(bar), "l"(POL_FIRST)
      : "memory");
}
__device__ __forceinline__ void tma_keep(const uint8_t* base, int row) {
  asm volatile(
      "{\n.reg .pred P;\nelect.sync _|P, 0xffffffff;\n"
      "@P cp.async.bulk.prefetch.L2.global.L2::cache_hint [%0], 2048, %1;\n}" ::"l"(base + (size_t)(uint32_t)row * 128),
      "l"(POL_NORMAL)
      : "memory");
}
__device__ __forceinline__ void tma_issue2(uint32_t dst, const CUtensorMap* tmK, const CUtensorMap* tmV, int c0, int row,
                                           uint32_t bar) {
  asm volatile(
      "{\n.reg .pred P;\nelect.sync _|P, 0xffffffff;\n"
      "@P mbarrier.arrive.expect_tx.shared::cta.b64 _, [%5], 4096;\n"
      "@P cp.async.bulk.tensor.2d.shared::cluster.global.tile.mbarrier::complete_tx::bytes.L2::cache_hint"
      " [%0], [%1, {%3, %4}], [%5], %6;\n"
      "@P cp.async.bulk.tensor.2d.shared::cluster.global.tile.mbarrier::complete_tx::bytes.L2::cache_hint"
      " [%7], [%2, {%3, %4}], [%5], %6;\n}" ::"r"(dst), "l"(tmK), "l"(tmV), "r"(c0), "r"(row), "r"(bar), "l"(POL_FIRST),
      "r"(dst + 2048)
      : "memory");
}
__device__ __forceinline__ uint32_t uni(uint32_t v) { return __shfl_sync(0xffffffffu, v, 0); }
__device__ __forceinline__ uint32_t ticket_take(uint32_t addr) {
  uint32_t v = 0;
  asm volatile("{\n.reg .pred P;\nelect.sync _|P, 0xffffffff;\n@P atom.shared.add.u32 %0, [%1], 1;\n}"
               : "+r"(v) : "r"(addr) : "memory");
  return v;
}
__device__ __forceinline__ uint32_t ticket_bcast(uint32_t v) { return __reduce_max_sync(0xffffffffu, v); }
__device__ __forceinline__ uint32_t pack_bf16(float lo, float hi) {
  uint32_t r;
  asm("cvt.rn.bf16x2.f32 %0, %1, %2;" : "=r"(r) : "f"(hi), "f"(lo));
  return r;
}
__device__ __forceinline__ float bf16r(float x) { return __uint_as_float(pack_bf16(0.f, x) & 0xffff0000u); }
__device__ __forceinline__ float bflo(uint32_t w) { return __uint_as_float(w << 16); }
__device__ __forceinline__ float bfhi(uint32_t w) { return __uint_as_float(w & 0xffff0000u); }

__device__ __forceinline__ uint32_t ll_tag(uint32_t epoch, uint32_t stage) { return 1 + (epoch * 3 + stage) % 255; }
__device__ __forceinline__ float ll_trunc(float v) { return __uint_as_float(__float_as_uint(v) & 0xffffff00u); }
__device__ __forceinline__ void ll_st(uint32_t* p, float v, uint32_t tag) {
  asm volatile("st.relaxed.gpu.global.u32 [%0], %1;" ::"l"(p), "r"((__float_as_uint(v) & 0xffffff00u) | tag) : "memory");
}
__device__ __forceinline__ void aux_sync() { asm volatile("bar.sync 1, 128;" ::: "memory"); }
__device__ __forceinline__ void stamp(int) {}
__device__ __forceinline__ void stamp2(int, int) {}

struct Acc { float o0, o1, o2, o3, m, l; };

__device__ __forceinline__ uint32_t softmax8(float s0, float s1, float s2, float s3, Acc& a, int lane) {
  const float sc = ((lane & 16) ? (s1 + s2) : (s0 + s3)) * SCALE_LOG2;
  if (__any_sync(0xffffffffu, sc > a.m)) {
    float mx = fmaxf(sc, __shfl_xor_sync(0xffffffffu, sc, 4));
    mx = fmaxf(mx, __shfl_xor_sync(0xffffffffu, mx, 8));
    mx = fmaxf(mx, __shfl_xor_sync(0xffffffffu, mx, 16));
    mx = fmaxf(mx, a.m);
    const float alpha = ex2(a.m - mx);
    a.o0 *= alpha; a.o1 *= alpha; a.o2 *= alpha; a.o3 *= alpha; a.l *= alpha;
    a.m = mx;
  }
  const float p = ex2(sc - a.m);
  a.l += p;
  uint32_t pp, pk;
  asm("cvt.rn.bf16x2.f32 %0, %1, %1;" : "=r"(pp) : "f"(p));
  asm volatile("movmatrix.sync.aligned.m8n8.trans.b16 %0, %1;" : "=r"(pk) : "r"(pp));
  return pk;
}
__device__ __forceinline__ uint32_t qk_reg(const uint32_t* kf, uint32_t qaddr, Acc& a, int lane) {
  float s0 = 0.f, s1 = 0.f, s2 = 0.f, s3 = 0.f;
  {
    const uint4 q = lds128(qaddr);
    mma16816(s0, s1, s2, s3, kf + 0, q.x, q.y);
    mma16816(s0, s1, s2, s3, kf + 4, q.z, q.w);
  }
  {
    const uint4 q = lds128(qaddr + 128);
    mma16816(s0, s1, s2, s3, kf + 8, q.x, q.y);
    mma16816(s0, s1, s2, s3, kf + 12, q.z, q.w);
  }
  return softmax8(s0, s1, s2, s3, a, lane);
}
__device__ __forceinline__ void pv_q(const uint32_t* vf, int j, uint32_t pk, Acc& a, int lane) {
  const int g = lane >> 2;
  const bool cm = ((g & 1) == 0) == ((lane & 2) == 0);
  const bool mine = (g >> 1) == j;
  mma16816(a.o0, a.o1, a.o2, a.o3, vf, (mine && cm) ? pk : 0u, (mine && !cm) ? pk : 0u);
}
__device__ __forceinline__ void pv_reg(const uint32_t* vf, uint32_t pk, Acc& a, int lane) {
#pragma unroll
  for (int j = 0; j < 4; j++) pv_q(vf + 4 * j, j, pk, a, lane);
}

__device__ __forceinline__ void side_fill_w(const CUtensorMap* tmK, const CUtensorMap* tmV, uint32_t sb, uint32_t side,
                                            uint32_t wp, int lane, uint32_t i, uint32_t b, int dep) {
  const uint4 p = lds128(wp + 16);
  const uint32_t slot = uni((p.z & 255) + i * ((p.z >> 8) & 255));
  const int row = (int)(p.y + i * ((p.z >> 16) & 255) + b * TPB) * 16;
  tma_issue2(side + slot * 4096, tmK, tmV, dep, row, sb + OFF_SBAR + slot * 8);
}
__device__ __forceinline__ void stream_prologue(const CUtensorMap* tmK, const CUtensorMap* tmV, const uint32_t sb,
                                                const uint32_t side, const int w, const int lane) {
  const uint32_t ring = sb + OFF_RING + w * RING_W;
  const uint32_t rbar = sb + OFF_RBAR + w * 32;
  const uint32_t wp = sb + OFF_WP + w * 32;
  const uint4 p = lds128(wp + 16);
  const uint32_t nside = p.z >> 24;
  if (lane == 0) {
    mbar_expect_tx(rbar, 2048);      tma_load(ring, tmK, 0, (int)p.w * 16, rbar);
    mbar_expect_tx(rbar + 8, 2048);  tma_load(ring + 2048, tmV, 0, (int)p.w * 16, rbar + 8);
    mbar_expect_tx(rbar + 16, 2048); tma_load(ring + 4096, tmK, 0, (int)(p.w + 1) * 16, rbar + 16);
    if (CFG_SLOTS == 4) { mbar_expect_tx(rbar + 24, 2048); tma_load(ring + 6144, tmV, 0, (int)(p.w + 1) * 16, rbar + 24); }
  }
  __syncwarp();
  side_fill_w(tmK, tmV, sb, side, wp, lane, 0, 0, 0);
  uint32_t sis = 1;
  if (nside > 1) side_fill_w(tmK, tmV, sb, side, wp, lane, sis++, 0, 0);
  int it = 0;
  while (!__all_sync(0xffffffffu, mbar_test(sb + BAR_Q1, 0))) {
    if (sis < nside &&
        __all_sync(0xffffffffu, mbar_test(sb + OFF_SBAR + ((p.z & 255) + (sis - 2) * ((p.z >> 8) & 255)) * 8, 0)))
      side_fill_w(tmK, tmV, sb, side, wp, lane, sis++, 0, 0);
    else
      __nanosleep(40);
    if (++it > SPIN_LIMIT) __trap();
  }
  if (lane == 0) sts32(sb + OFF_HELD + w * 4, sis);
  __syncwarp();
}

__device__ __forceinline__ void stream_warp(const CUtensorMap* tmK, const CUtensorMap* tmV, const uint32_t sb,
                                            const uint32_t side, const int w, const int lane, const Params& prm) {
  const uint32_t& zero = prm.zero;
  const uint32_t ring = sb + OFF_RING + w * RING_W;
  const uint32_t rbar = sb + OFF_RBAR + w * 32;
  const uint32_t wp = sb + OFF_WP + w * 32;
  uint32_t laneK, laneV;
  {
    const int mat = lane >> 3, i = lane & 7;
    const int hk = (mat & 1) ? (i < 4) : (i >= 4);
    const int rk = 2 * i + hk;
    laneK = ring + rk * 128 + (((mat >> 1) ^ (rk & 7)) << 4);
    laneV = laneK ^ (((mat ^ (mat >> 1)) & 1) << 7);
  }
  const uint32_t qoff = lds128(wp + 16).x + (((lane >> 2) & 1) * 4 + (lane & 3)) * 16;

  uint32_t kv[RP][32];
  Acc cur, oth;
  cur.o0 = cur.o1 = cur.o2 = cur.o3 = cur.l = 0.f; cur.m = -INFINITY;
  oth = cur;
  uint32_t st = 0;
  uint32_t csp = 0;
  uint32_t d0, d1;
  uint32_t ev;
  uint32_t ss = 0;
  uint32_t mseg = lds32(wp);
  const uint32_t ctrM = lds32(wp + 4);
  uint32_t tn = ticket_take(ctrM);

  auto ensure = [&](uint32_t b) {
    const uint32_t sw = b ^ ((st >> 11) & 1);
    static_assert(ST_CURB == 1u << 11, "");
    asm volatile(
        "{\n.reg .pred p;\n.reg .f32 t;\nsetp.eq.u32 p, %12, 0;\n@p bra.uni SKIP;\n"
        "mov.f32 t, %0;\nmov.f32 %0, %6;\nmov.f32 %6, t;\nmov.f32 t, %1;\nmov.f32 %1, %7;\nmov.f32 %7, t;\n"
        "mov.f32 t, %2;\nmov.f32 %2, %8;\nmov.f32 %8, t;\nmov.f32 t, %3;\nmov.f32 %3, %9;\nmov.f32 %9, t;\n"
        "mov.f32 t, %4;\nmov.f32 %4, %10;\nmov.f32 %10, t;\nmov.f32 t, %5;\nmov.f32 %5, %11;\nmov.f32 %11, t;\n"
        "SKIP:\n}"
        : "+f"(cur.o0), "+f"(cur.o1), "+f"(cur.o2), "+f"(cur.o3), "+f"(cur.m), "+f"(cur.l), "+f"(oth.o0), "+f"(oth.o1),
          "+f"(oth.o2), "+f"(oth.o3), "+f"(oth.m), "+f"(oth.l)
        : "r"(sw));
    st ^= sw << 11;
  };
  auto gate = [&](uint32_t b) {
    const uint32_t bit = b ? ST_R1 : ST_R0;
    if (!(st & bit)) { mbar_wait(sb + (b ? BAR_R1 : BAR_R0), 0); st |= bit; }
  };
  auto issue = [&](const CUtensorMap* tm, uint32_t dst, uint32_t bar, uint32_t d, int dep) {
    const int row = (int)(d & D_TILE) * 16;
    tma_issue(dst, tm, dep, row, bar);
    if (CFG_PFDELAY == 0 && (d & D_PF)) tma_keep(tm == tmK ? prm.kbytes : prm.vbytes, row);
  };
  auto keep_late = [&](const uint8_t* base, uint32_t d) {
    if (d & D_PF) tma_keep(base, (int)(d & D_TILE) * 16);
  };
  auto advance = [&]() {
    csp += 2048;
    if ((csp & 0x1800) == 0x1800) csp = (csp & 1) ^ 1;
  };
  auto reg_desc = [&](uint32_t i) { return D_VALID | D_REG | D_B1 | D_PAST0 | (lds128(wp + 16).w + TPB + i); };
  auto grab = [&]() -> uint32_t {
    const uint4 P = lds128(mseg);
    const uint32_t t = ticket_bcast(tn);
    uint32_t d;
    bool held = false;
    if (t < P.x) {
      d = P.y + t;
      if (t >= P.z) d |= D_PF;
    } else {
      const uint32_t s0 = lds32(wp);
      while (true) {
        const uint32_t si = (mseg - s0) >> 4;
        if (si >= 6) { d = D_PASTS | D_END; break; }
        const uint4 M = lds128(mseg);
        if (t < M.x) { d = (M.y + t) | (t >= M.z ? D_PF : 0u); break; }
        if (si == 3 && !(st & ST_INJ)) {
          st = (st | ST_INJ | ST_INJ2) & ~ST_SONLY;
          ev |= D_VALID;
          held = true;
          d = reg_desc(0);
          break;
        }
        mseg += 16;
      }
    }
    if (held) tn = t; else tn = ticket_take(ctrM);
    return d;
  };
  auto qk_smem = [&](Acc& A, uint32_t la, uint32_t qa, auto mid) -> uint32_t {
    float s0 = 0.f, s1 = 0.f, s2 = 0.f, s3 = 0.f;
    uint32_t f[8];
    ldsm4(f, la); ldsm4(f + 4, la ^ 32);
    {
      const uint4 q = lds128(qa);
      mma16816v(s0, s1, s2, s3, f, q.x, q.y);
      mma16816v(s0, s1, s2, s3, f + 4, q.z, q.w);
    }
    ldsm4(f, la ^ 64); ldsm4(f + 4, la ^ 96);
    mid(f[7]);
    {
      const uint4 q = lds128(qa + 128);
      mma16816v(s0, s1, s2, s3, f, q.x, q.y);
      mma16816v(s0, s1, s2, s3, f + 4, q.z, q.w);
    }
    return softmax8(s0, s1, s2, s3, A, lane);
  };
  auto pv_smem = [&](Acc& A, uint32_t la, uint32_t pk, auto mid) {
    const int g = lane >> 2;
    const bool cm = ((g & 1) == 0) == ((lane & 2) == 0);
    const uint32_t b0 = cm ? pk : 0u, b1 = cm ? 0u : pk;
    uint32_t f[8];
    ldsm4t(f, la); ldsm4t(f + 4, la ^ 32);
    mma16816v(A.o0, A.o1, A.o2, A.o3, f, (g >> 1) == 0 ? b0 : 0u, (g >> 1) == 0 ? b1 : 0u);
    mma16816v(A.o0, A.o1, A.o2, A.o3, f + 4, (g >> 1) == 1 ? b0 : 0u, (g >> 1) == 1 ? b1 : 0u);
    ldsm4t(f, la ^ 64); ldsm4t(f + 4, la ^ 96);
    mid(f[7]);
    mma16816v(A.o0, A.o1, A.o2, A.o3, f, (g >> 1) == 2 ? b0 : 0u, (g >> 1) == 2 ? b1 : 0u);
    mma16816v(A.o0, A.o1, A.o2, A.o3, f + 4, (g >> 1) == 3 ? b0 : 0u, (g >> 1) == 3 ? b1 : 0u);
  };
#define LOG_STEP(kind)
  auto ring_step = [&](const uint32_t d2) {
    csp = uni(csp);
    uint32_t so = csp & 0x1800, bar = rbar + (csp >> 8);
    mbar_wait(bar, csp & 1);
    const uint32_t pk = qk_smem(cur, laneK + so, qoff + ((d0 >> 8) & 256), [&](uint32_t last) {
      if (d1 & D_VALID) issue(tmV, ring + so, bar, d1, dep_zero(last, zero));
      if (CFG_PFDELAY == 1) keep_late(prm.kbytes, d1);
      if (CFG_PFDELAY == 2) keep_late(prm.vbytes, d0);
    });
    advance();
    so = csp & 0x1800; bar = rbar + (csp >> 8);
    mbar_wait(bar, csp & 1);
    pv_smem(cur, laneV + so, pk, [&](uint32_t last) {
      if (d2 & D_VALID) issue(tmK, ring + so, bar, d2, dep_zero(last, zero));
      if (CFG_PFDELAY == 1) keep_late(prm.vbytes, d1);
      if (CFG_PFDELAY == 2) keep_late(prm.kbytes, d1);
    });
    LOG_STEP(2u);
    advance();
    d0 = d1; d1 = d2;
  };
  auto reg_step = [&](uint32_t* kf, uint32_t* vf, uint32_t b, bool staticNext, uint32_t dstatic) {
    const uint32_t d2 = staticNext ? dstatic : grab();
    csp = uni(csp);
    uint32_t so = csp & 0x1800, bar = rbar + (csp >> 8);
    mbar_wait(bar, csp & 1);
    {
      const uint32_t la = laneK + so;
      ldsm4(kf + 0, la); ldsm4(kf + 4, la ^ 32); ldsm4(kf + 8, la ^ 64); ldsm4(kf + 12, la ^ 96);
      if (d1 & D_VALID) issue(tmV, ring + so, bar, d1, dep_zero(kf[15], zero));
    }
    advance();
    const uint32_t pk = qk_reg(kf, qoff + b * 256, cur, lane);
    so = csp & 0x1800; bar = rbar + (csp >> 8);
    mbar_wait(bar, csp & 1);
    {
      const uint32_t la = laneV + so;
      ldsm4t(vf + 0, la); ldsm4t(vf + 4, la ^ 32); ldsm4t(vf + 8, la ^ 64); ldsm4t(vf + 12, la ^ 96);
      if (d2 & D_VALID) issue(tmK, ring + so, bar, d2, dep_zero(vf[15], zero));
    }
    pv_reg(vf, pk, cur, lane);
    LOG_STEP(2u);
    advance();
    d0 = d1; d1 = d2;
  };
  auto flush = [&](uint32_t b, uint32_t area, uint32_t bar) {
    ensure(b);
    float l = cur.l;
    l += __shfl_xor_sync(0xffffffffu, l, 4);
    l += __shfl_xor_sync(0xffffffffu, l, 8);
    l += __shfl_xor_sync(0xffffffffu, l, 16);
    const uint32_t e = area + ((lane & 3) * 16 + (lane >> 2)) * 4;
    stsf(e, cur.o0); stsf(e + 256, cur.o1); stsf(e + 32, cur.o2); stsf(e + 288, cur.o3);
    if (lane == 0) { stsf(area + 512, cur.m); stsf(area + 516, l); }
    __syncwarp();
    if (lane == 0) mbar_arrive(bar);
    cur.o0 = cur.o1 = cur.o2 = cur.o3 = cur.l = 0.f; cur.m = -INFINITY;
  };
  auto side_fill = [&](uint32_t i, uint32_t b, int dep) { side_fill_w(tmK, tmV, sb, side, wp, lane, i, b, dep); };
  const uint32_t pzu = uni(lds128(wp + 16).z), kblk = uni(lds32(wp) + 112);
  auto side_try = [&](const uint32_t j, const bool force) -> bool {
    const uint32_t bit = 1u << j;
    const uint32_t slot = (pzu & 255) + j * ((pzu >> 8) & 255);
    const uint32_t bar = sb + OFF_SBAR + slot * 8;
    const uint32_t b = (ss >> (SS_B + j)) & 1;
    bool cyc;
    if (ss & (bit << SS_F)) {
      const uint32_t par = (ss >> (SS_P + j)) & 1;
      if (force) mbar_wait(bar, par);
      else if (!__all_sync(0xffffffffu, mbar_test(bar, par))) return false;
      cyc = (ss & (bit << SS_K)) != 0;
      ss ^= (bit << SS_F) | (bit << SS_P);
    } else {
      if (!(st & (b ? ST_R1 : ST_R0))) {
        if (!force) return false;
        gate(b);
      }
      cyc = true;
      ss &= ~((bit << SS_H0) | (bit << SS_H1));
    }
    const uint4 kb = lds128(kblk);
    uint32_t u = 0;
    if (cyc) u = ticket_take(kb.w + b * 32);
    const uint32_t delta = side + slot * 4096 - ring;
    auto next_load = [&](uint32_t last) {
      if (cyc) {
        u = ticket_bcast(u);
        const int dep = dep_zero(last, zero);
        if (u < kb.x) {
          const int row = (int)(kb.y + b * TPB - u) * 16;
          tma_issue2(ring + delta, tmK, tmV, dep, row, bar);
          ss |= (bit << SS_F) | (bit << SS_K);
        } else if (!b) {
          side_fill(j, 1, dep);
          ss = (ss & ~(bit << SS_K)) | (bit << SS_F) | (bit << SS_B);
        } else {
          ss &= ~(bit << SS_K);
        }
      } else {
        ss |= bit << (b ? SS_H1 : SS_H0);
      }
    };
    if (b == ((st & ST_CURB) ? 1u : 0u)) {
      const uint32_t pk = qk_smem(cur, laneK + delta, qoff + b * 256, [&](uint32_t) {});
      pv_smem(cur, laneV + delta + 2048, pk, next_load);
    } else {
      const uint32_t pk = qk_smem(oth, laneK + delta, qoff + b * 256, [&](uint32_t) {});
      pv_smem(oth, laneV + delta + 2048, pk, next_load);
    }
    LOG_STEP(3u);
    return true;
  };

  ev = 0;
  uint32_t sfull;
  {
    const uint4 p = lds128(wp + 16);
    const uint32_t nside = p.z >> 24;
    sfull = (1u << nside) - 1;
    ss = sfull << SS_F;
    uint32_t sis = lds32(sb + OFF_HELD + w * 4);
    d0 = D_VALID | D_REG | D_B0 | p.w;
    d1 = D_VALID | D_REG | D_B0 | (p.w + 1);
#pragma unroll
    for (int i = 0; i < RP; i++) {
      if (sis < nside) side_fill(sis++, 0, 0);
      reg_step(&kv[i][0], &kv[i][16], 0, i + 2 < RP, D_VALID | D_REG | D_B0 | (lds128(wp + 16).w + i + 2));
    }
    while (sis < nside) side_fill(sis++, 0, 0);
  }
  ev = D_VALID | D_END;
  while (true) {
    uint32_t d2;
    if (d0 & ev) {
      if ((d0 & ev & ~(D_B0 | D_B1)) == 0) {
        ensure((d0 >> 16) & 1);
        ev ^= D_B0 | D_B1;
        d2 = grab();
      } else {
        const bool sonly = (d0 & ev & ~D_VALID) == 0 && (st & ST_SONLY);
        if (sonly) {
        } else if (!(st & ST_R0)) {
          if ((st & ST_FL0) && __all_sync(0xffffffffu, mbar_test(sb + BAR_R0, 0))) st |= ST_R0;
        } else if (!(st & ST_R1)) {
          if ((st & ST_FL1) && __all_sync(0xffffffffu, mbar_test(sb + BAR_R1, 0))) st |= ST_R1;
        }
        {
          const uint32_t sF = (ss >> SS_F) & 31, sH0 = (ss >> SS_H0) & 31, sH1 = (ss >> SS_H1) & 31;
          uint32_t need = 0;
          if (sonly) {}
          else if (!(st & ST_FL0)) { if (d0 & D_PAST0) need = sF; }
          else if (!(st & ST_FL1)) { if (d0 & D_PAST1) need = sfull & ~sH1; }
          else if (d0 & D_END) need = sF | sH0 | sH1;
          const bool force = need != 0;
          uint32_t cand = force ? need : (sF | ((st & ST_R0) ? sH0 : 0u) | ((st & ST_R1) ? sH1 : 0u));
          int budget = force ? 1 : CFG_SIDE_MAX;
          while (cand && budget) {
            if (CFG_SIDE_EVERY > 1 && !force && (d0 & D_VALID) && ((st >> SH_SKIP) & 7) < CFG_SIDE_EVERY - 1 &&
                (!CFG_RING_PRIO || __all_sync(0xffffffffu, mbar_test(rbar + (csp >> 8), csp & 1)))) {
              st += 1u << SH_SKIP;
              break;
            }
            st &= ~(7u << SH_SKIP);
            const uint32_t j = __ffs(cand) - 1;
            cand &= cand - 1;
            if (side_try(j, force)) budget--;
          }
          if (force) { ev |= D_VALID | D_END; st &= ~ST_SONLY; continue; }
        }
        if (sonly) {
          const uint32_t act = (ss >> SS_F) | ((st & ST_R0) ? (ss >> SS_H0) : 0u) | ((st & ST_R1) ? (ss >> SS_H1) : 0u);
          if (!(act & 31)) { ev &= ~D_VALID; st &= ~ST_SONLY; }
          d2 = grab();
          goto step;
        }
        {
        bool redo = true;
        if (!(st & ST_FL0) && (d0 & D_PAST0)) {
          flush(0, sb + OFF_PART + w * 528, sb + BAR_P0);
          st |= ST_FL0;
        } else if (d0 & D_REG) {
          gate(0);
#pragma unroll
          for (int i = 0; i < RP; i++) {
            if (i == 0) ensure(1);
            const uint32_t pk = qk_reg(&kv[i][0], qoff, oth, lane);
            pv_reg(&kv[i][16], pk, oth, lane);
            reg_step(&kv[i][0], &kv[i][16], 1, i + 2 < RP, reg_desc(i + 2));
          }
        } else if (!(st & ST_FL1) && (d0 & D_PAST1)) {
          flush(1, sb + OFF_PART + w * 528, sb + BAR_P0 + 8);
          st |= ST_FL1;
        } else if (!(st & ST_FL2) && (d0 & D_PAST2)) {
          gate(1);
          flush(0, sb + OFF_PART + w * 528, sb + BAR_P0 + 16);
          st |= ST_FL2;
        } else if (!(st & ST_REGC) && ((st & ST_R1) || (d0 & D_END))) {
          gate(1);
          ensure(1);
#pragma unroll
          for (int i = 0; i < RP; i++) {
            const uint32_t pk = qk_reg(&kv[i][0], qoff + 256, cur, lane);
            pv_reg(&kv[i][16], pk, cur, lane);
          }
          st |= ST_REGC;
        } else if (d0 & D_END) {
          break;
        } else {
          redo = false;
        }
        if (redo) { ev |= D_VALID | D_END; st &= ~ST_SONLY; continue; }
        if (d0 & D_N0) gate(0);
        if (d0 & D_N1) gate(1);
        ensure((d0 >> 16) & 1);
        bool forced = false;
        if (st & ST_INJ2) {
          st &= ~ST_INJ2;
          d2 = reg_desc(1);
          forced = true;
        } else if ((st & (ST_R0 | ST_INJ)) == ST_R0) {
          st |= ST_INJ | ST_INJ2;
          d2 = reg_desc(0);
          forced = true;
        }
        ev = D_REG | D_END | ((st & ST_CURB) ? D_B0 : D_B1) | ((st & ST_FL0) ? 0u : D_PAST0) |
             ((st & ST_FL1) ? 0u : D_PAST1) | ((st & ST_FL2) ? 0u : D_PAST2) | ((st & ST_R0) ? 0u : D_N0) |
             ((st & ST_R1) ? 0u : D_N1);
        const uint32_t act = (ss >> SS_F) | ((st & ST_R0) ? (ss >> SS_H0) : 0u) | ((st & ST_R1) ? (ss >> SS_H1) : 0u);
        st &= ~ST_SONLY;
        if ((st & ST_INJ2) || ((st & (ST_R1 | ST_REGC)) == ST_R1)) ev |= D_VALID;
        else if (act & 31) { ev |= D_VALID; st |= ST_SONLY; }
        if (((st & ST_FL0) && !(st & ST_R0)) || ((st & ST_FL1) && !(st & ST_R1))) ev |= 1;
        if (!forced) d2 = grab();
        }
      }
    } else {
      d2 = grab();
    }
  step:
    ring_step(d2);
    if (CFG_IDLE) __nanosleep(CFG_IDLE);
    if (CFG_IDLE_WAIT && (ev & 1)) __nanosleep(CFG_IDLE_WAIT);
  }
  flush(1, ring, sb + BAR_P0 + 24);
}

__device__ __forceinline__ void aux_layernorm(const uint32_t sb, const uint32_t dst, const int t, float x0, float x1,
                                              float x2, float x3) {
  float s = (x0 + x1) + (x2 + x3);
#pragma unroll
  for (int o = 16; o; o >>= 1) s += __shfl_xor_sync(0xffffffffu, s, o);
  const float mw = s * (1.f / 128);
  float v = ((x0 - mw) * (x0 - mw) + (x1 - mw) * (x1 - mw)) + ((x2 - mw) * (x2 - mw) + (x3 - mw) * (x3 - mw));
#pragma unroll
  for (int o = 16; o; o >>= 1) v += __shfl_xor_sync(0xffffffffu, v, o);
  if ((t & 31) == 0) { stsf(sb + OFF_RED + (t >> 5) * 4, mw); stsf(sb + OFF_RED + 16 + (t >> 5) * 4, v); }
  aux_sync();
  const uint4 rs = lds128(sb + OFF_RED), rv = lds128(sb + OFF_RED + 16);
  const float m0 = __uint_as_float(rs.x), m1 = __uint_as_float(rs.y), m2 = __uint_as_float(rs.z), m3 = __uint_as_float(rs.w);
  const float mean = ((m0 + m1) + (m2 + m3)) * 0.25f;
  const float var = (((__uint_as_float(rv.x) + __uint_as_float(rv.y)) + (__uint_as_float(rv.z) + __uint_as_float(rv.w))) +
                     128.f * (((m0 - mean) * (m0 - mean) + (m1 - mean) * (m1 - mean)) +
                              ((m2 - mean) * (m2 - mean) + (m3 - mean) * (m3 - mean)))) * (1.f / DM);
  const float m = bf16r(mean);
  const float den = bf16r(__fsqrt_rn(bf16r(bf16r(var) + 1e-5f)));
  sts32(dst + t * 8, pack_bf16(__fdividef(bf16r(x0 - m), den), __fdividef(bf16r(x1 - m), den)));
  sts32(dst + t * 8 + 4, pack_bf16(__fdividef(bf16r(x2 - m), den), __fdividef(bf16r(x3 - m), den)));
  aux_sync();
}
__device__ __forceinline__ void ldsm2t(uint32_t* r, uint32_t addr) {
  asm volatile("ldmatrix.sync.aligned.m8n8.x2.trans.shared.b16 {%0,%1}, [%2];" : "=r"(r[0]), "=r"(r[1]) : "r"(addr) : "memory");
}
__device__ __forceinline__ void mma1688(float& d0, float& d1, float& d2, float& d3, const uint32_t* a, uint32_t b0) {
  asm("mma.sync.aligned.m16n8k8.row.col.f32.bf16.bf16.f32 {%0,%1,%2,%3}, {%4,%5}, {%6}, {%0,%1,%2,%3};"
      : "+f"(d0), "+f"(d1), "+f"(d2), "+f"(d3) : "r"(a[0]), "r"(a[1]), "r"(b0));
}
__device__ __forceinline__ void cp16(uint32_t dst, const void* src) {
  asm volatile("cp.async.cg.shared.global.L2::cache_hint [%0], [%1], 16, %2;" ::"r"(dst), "l"(src), "l"(POL_FIRST) : "memory");
}
__device__ __forceinline__ void cp_wait_all() { asm volatile("cp.async.wait_all;" ::: "memory"); }
__device__ __forceinline__ void gemv_mma(float& c0, float& c1, float& c2, float& c3, uint32_t la, uint32_t astep,
                                         uint32_t xa, int nk) {
  float e0 = 0.f, e1 = 0.f, e2 = 0.f, e3 = 0.f;
#pragma unroll 1
  for (int k = 0; k < nk; k += 2) {
    uint32_t a[4], a2[4];
    ldsm4t(a, la);
    ldsm4t(a2, la + astep);
    const uint32_t b0 = lds32(xa), b1 = lds32(xa + 16), b2 = lds32(xa + 32), b3 = lds32(xa + 48);
    mma16816(c0, c1, c2, c3, a, b0, b1);
    mma16816(e0, e1, e2, e3, a2, b2, b3);
    la += 2 * astep;
    xa += 64;
  }
  c0 += e0; c1 += e1; c2 += e2; c3 += e3;
}
__device__ __forceinline__ uint32_t ll_raw(const uint32_t* p) {
  uint32_t w;
  asm volatile("ld.relaxed.gpu.global.u32 %0, [%1];" : "=r"(w) : "l"(p) : "memory");
  return w;
}
__device__ __forceinline__ bool ll_ok(uint32_t w, uint32_t tag) { return (w & 255) == tag; }
__device__ __forceinline__ float ll_val(uint32_t w) { return __uint_as_float(w & 0xffffff00u); }
__device__ __forceinline__ void ll_backoff(int& it) {
  if (++it > SPIN_LIMIT) __trap();
  __nanosleep(40);
}
__device__ __forceinline__ float ll_wait1(const uint32_t* p, uint32_t tag) {
  int it = 0;
  while (true) {
    const uint32_t w = ll_raw(p);
    if (ll_ok(w, tag)) return ll_val(w);
    ll_backoff(it);
  }
}
__device__ __forceinline__ void ll_wait4(const uint32_t* p, uint32_t tag, float& x0, float& x1, float& x2, float& x3) {
  int it = 0;
  while (true) {
    uint32_t a, b, c, d;
    asm volatile("ld.relaxed.gpu.global.v4.u32 {%0,%1,%2,%3}, [%4];" : "=r"(a), "=r"(b), "=r"(c), "=r"(d) : "l"(p) : "memory");
    if (ll_ok(a, tag) && ll_ok(b, tag) && ll_ok(c, tag) && ll_ok(d, tag)) {
      x0 = ll_val(a); x1 = ll_val(b); x2 = ll_val(c); x3 = ll_val(d);
      return;
    }
    ll_backoff(it);
  }
}
__device__ __forceinline__ void ll_wait2s(const uint32_t* p, int stride, uint32_t tag, float& x0, float& x1) {
  int it = 0;
  while (true) {
    const uint32_t a = ll_raw(p), b = ll_raw(p + stride);
    if (ll_ok(a, tag) && ll_ok(b, tag)) { x0 = ll_val(a); x1 = ll_val(b); return; }
    ll_backoff(it);
  }
}
__device__ __forceinline__ float warp_sum4(float v0, float v1, float v2, float v3, int lane) {
  const bool h16 = lane & 16, h8 = lane & 8;
  const float k0 = (h16 ? v2 : v0) + __shfl_xor_sync(0xffffffffu, h16 ? v0 : v2, 16);
  const float k1 = (h16 ? v3 : v1) + __shfl_xor_sync(0xffffffffu, h16 ? v1 : v3, 16);
  float k = (h8 ? k1 : k0) + __shfl_xor_sync(0xffffffffu, h8 ? k0 : k1, 8);
  k += __shfl_xor_sync(0xffffffffu, k, 4);
  k += __shfl_xor_sync(0xffffffffu, k, 2);
  k += __shfl_xor_sync(0xffffffffu, k, 1);
  return k;
}
__device__ __forceinline__ void hint_arrive(unsigned int* c, const int t) {
  aux_sync();
  if (t == 0) asm volatile("red.relaxed.gpu.global.add.u32 [%0], 1;" ::"l"(c) : "memory");
}
__device__ __forceinline__ void hint_wait(const unsigned int* c, uint32_t target, const int t) {
  if (t == 0) {
    int it = 0;
    while (true) {
      uint32_t v;
      asm volatile("ld.relaxed.gpu.global.u32 %0, [%1];" : "=r"(v) : "l"(c) : "memory");
      if ((int)(v - target) >= 0) break;
      if (++it > SPIN_LIMIT) __trap();
      __nanosleep(CFG_HINT_SLEEP);
    }
  }
  aux_sync();
}
__device__ __forceinline__ void aux_qproj(const uint32_t sb, const int t, int h, int r, uint32_t xn0, uint32_t xn1, int b0,
                                          int nb, uint32_t tag) {
  const int wq = t >> 5, lane = t & 31, mat = lane >> 3, g = lane >> 2;
  const int row = (wq >> 1) * 256 + (mat >> 1) * 8 + (lane & 7), ch = 2 * (wq & 1) + (mat & 1);
  float c0 = 0.f, c1 = 0.f, c2 = 0.f, c3 = 0.f;
  gemv_mma(c0, c1, c2, c3, sb + OFF_WQ + row * 64 + ((ch ^ ((row >> 1) & 3)) << 4), 1024,
           ((g & 1) ? xn1 : xn0) + ((wq >> 1) * 256 + 2 * (lane & 3)) * 2, 16);
  if ((lane & 3) == 0) {
    const uint32_t e = sb + SC_RED4 + ((wq >> 1) * 64 + (wq & 1) * 16 + g) * 4;
    stsf(e, c0); stsf(e + 32, c2); stsf(e + 128, c1); stsf(e + 160, c3);
  }
  aux_sync();
  if (t < 32 * nb)
    ll_st(&g_Q[b0 + (t >> 5)][h][r * 32 + (t & 31)], bf16r(ldsf(sb + SC_RED4 + t * 4) + ldsf(sb + SC_RED4 + (64 + t) * 4)), tag);
  aux_sync();
  if (t < nb) asm volatile("red.relaxed.gpu.global.add.u32 [%0], 1;" ::"l"(&g_cntQ[b0 + t][h]) : "memory");
}
__device__ __forceinline__ void qfrag_store(uint32_t qf, const int t, float q) {
  const int half = t >> 6, j = (t >> 4) & 3, k = t & 15;
  const uint32_t off = (j >> 1) * 128 + (half * 4 + ((k & 7) >> 1)) * 16 + ((j & 1) * 2 + (k >> 3)) * 4 + (k & 1) * 2;
  sts16(qf + off, (uint16_t)(__float_as_uint(q) >> 16));
}

__device__ __forceinline__ int aux_tid() {
  int t;
  asm volatile("mov.u32 %0, %%tid.x;" : "=r"(t));
  return t - 256;
}
#define AUX_STAGE() \
  t = aux_tid(); wq = t >> 5; lane = t & 31; mat = lane >> 3; g = lane >> 2; i8 = lane & 7

__device__ __forceinline__ void aux_chain(const Params& p, const uint32_t sb, const int c, const int b,
                                          const int layer, const uint32_t epoch, uint32_t area, uint32_t astride,
                                          uint32_t pbar) {
  const uint32_t tag = ll_tag(epoch, 1 + layer);
  const bool last = b && layer;
  const uint32_t use = 2 * (epoch - 1) + layer + 1;
  const int h = c >> 2, r = c & 3;
  int t, wq, lane, mat, g, i8;
  AUX_STAGE();
  const int nsrc = p.ht ? 5 : 4;
  if (t == 0) stamp2(b + 2 * layer, 0);
  mbar_wait(pbar, 0);
  if (t == 0) stamp(2 + 2 * (b + 2 * layer));
  {
    float M = -INFINITY;
#pragma unroll
    for (int k = 0; k < 8; k++) M = fmaxf(M, ldsf(area + k * astride + 512));
    M = ll_trunc(M);
    float O = 0.f, L = 0.f;
#pragma unroll 4
    for (int k = 0; k < 8; k++) {
      const float sc = ex2(ldsf(area + k * astride + 512) - M);
      O = fmaf(sc, ldsf(area + k * astride + t * 4), O);
      L = fmaf(sc, ldsf(area + k * astride + 516), L);
    }
    ll_st(&g_P[b][h][r][t], O, tag);
    if (t == 0) { ll_st(&g_P[b][h][r][128], M, tag); ll_st(&g_P[b][h][r][129], L, tag); }
  }
  hint_arrive(&g_cntP[b][h], t);
  hint_wait(&g_cntP[b][h], use * nsrc - (last ? 1 : 0), t);
  if (t == 0) stamp2(b + 2 * layer, 1);
  AUX_STAGE();
  {
    const int sl = lane < nsrc ? lane : 0;
    const uint32_t* P0 = &g_P[b][h][0][t];
    uint32_t wm, wl, w0, w1, w2, w3, w4;
    int it = 0;
    while (true) {
      wm = ll_raw(&g_P[b][h][sl][128]); wl = ll_raw(&g_P[b][h][sl][129]);
      w0 = ll_raw(P0); w1 = ll_raw(P0 + 132); w2 = ll_raw(P0 + 264); w3 = ll_raw(P0 + 396);
      w4 = ll_raw(P0 + (nsrc == 5 ? 528 : 0));
      const bool ok = ll_ok(wm, tag) && ll_ok(wl, tag) && ll_ok(w0, tag) && ll_ok(w1, tag) && ll_ok(w2, tag) &&
                      ll_ok(w3, tag) && ll_ok(w4, tag);
      if (__all_sync(0xffffffffu, ok)) break;
      ll_backoff(it);
    }
    const float ms = lane < nsrc ? ll_val(wm) : -INFINITY;
    float M = ms;
#pragma unroll
    for (int o = 4; o; o >>= 1) M = fmaxf(M, __shfl_xor_sync(0xffffffffu, M, o));
    M = __shfl_sync(0xffffffffu, M, 0);
    const float e = (lane < nsrc) ? ex2(ms - M) : 0.f;
    float L = e * ll_val(wl);
#pragma unroll
    for (int o = 4; o; o >>= 1) L += __shfl_xor_sync(0xffffffffu, L, o);
    L = __shfl_sync(0xffffffffu, L, 0);
    const float wgt = __fdividef(e, L);
    float o = __shfl_sync(0xffffffffu, wgt, 0) * ll_val(w0);
    o = fmaf(__shfl_sync(0xffffffffu, wgt, 1), ll_val(w1), o);
    o = fmaf(__shfl_sync(0xffffffffu, wgt, 2), ll_val(w2), o);
    o = fmaf(__shfl_sync(0xffffffffu, wgt, 3), ll_val(w3), o);
    o = fmaf(__shfl_sync(0xffffffffu, wgt, 4), ll_val(w4), o);
    sts16(sb + SC_O + t * 2, (uint16_t)(pack_bf16(o, 0.f) & 0xffffu));
  }
  aux_sync();
  if (t == 0) stamp2(b + 2 * layer, 2);
  AUX_STAGE();
#pragma unroll 1
  for (int m = 0; m < 2; m++) {
    const int mt = 2 * wq + m;
    float c0 = 0.f, c1 = 0.f, c2 = 0.f, c3 = 0.f;
    gemv_mma(c0, c1, c2, c3, sb + OFF_WO + ((mat >> 1) * 8 + i8) * 256 + (((2 * mt + (mat & 1)) ^ i8) << 4), 4096,
             sb + SC_O + (lane & 3) * 4, 8);
    if ((lane & 3) < 2) ll_st(&g_Z[b][h][r * 128 + mt * 16 + g + 8 * (lane & 1)], (lane & 1) ? c2 : c0, tag);
  }
  hint_arrive(&g_cntZ[b][r], t);
  if (t == 0) stamp2(b + 2 * layer, 3);
  AUX_STAGE();
  hint_wait(&g_cntZ[b][c >> 5], use * NH - CFG_HINT_K, t);
  if (wq == 0) {
    float z0, z1, z2, z3;
    ll_wait4(&g_Z[b][lane][4 * c], tag, z0, z1, z2, z3);
    __syncwarp();
    const float xres = bf16r(ldsf(sb + OFF_XRES + (b * 4 + mat) * 4) + bf16r(warp_sum4(z0, z1, z2, z3, lane)));
    __syncwarp();
    if (i8 == 0) {
      stsf(sb + OFF_XRES + (b * 4 + mat) * 4, xres);
      ll_st(&g_X1[b][4 * c + mat], xres, tag);
    }
  }
  hint_arrive(&g_cntX1[b], t);
  if (t == 0) stamp2(b + 2 * layer, 4);
  AUX_STAGE();
  const int ng = ffn_groups(c);
  {
    float x0, x1, x2, x3;
    if (!last) hint_wait(&g_cntX1[b], use * NMAIN - 4 * CFG_HINT_K, t);
    ll_wait4(&g_X1[b][4 * t], tag, x0, x1, x2, x3);
    if (t == 0) stamp2(b + 2 * layer, 5);
    aux_layernorm(sb, sb + OFF_XN, t, x0, x1, x2, x3);
  }
  AUX_STAGE();
#pragma unroll 1
  for (int gi = 0; gi < ng; gi++) {
    float c0 = 0.f, c1 = 0.f, c2 = 0.f, c3 = 0.f;
    gemv_mma(c0, c1, c2, c3, sb + OFF_WF + gi * WF_BYTES + (mat & 1) * 8192 + (wq * 128 + (mat >> 1) * 8 + i8) * 16, 256,
             sb + OFF_XN + (wq * 128 + 2 * (lane & 3)) * 2, 8);
    if ((lane & 3) == 0) {
      const uint32_t e = sb + SC_RED4 + ((gi * 4 + wq) * 16 + g) * 4;
      stsf(e, c0); stsf(e + 32, c2);
    }
  }
  aux_sync();
  if (t < 8 * ng) {
    const uint32_t e = sb + SC_RED4 + ((t >> 3) * 64 + (t & 7)) * 4;
    const float gt = ldsf(e) + ldsf(e + 64) + ldsf(e + 128) + ldsf(e + 192);
    const float up = ldsf(e + 32) + ldsf(e + 96) + ldsf(e + 160) + ldsf(e + 224);
    sts16(sb + SC_H + t * 2, (uint16_t)(pack_bf16(bf16r(gt) * bf16r(up), 0.f) & 0xffffu));
  }
  aux_sync();
  if (t == 0) stamp2(b + 2 * layer, 6);
  AUX_STAGE();
#pragma unroll 1
  for (int m = 0; m < 8; m += 2) {
    const int mt = 8 * wq + m;
    float c0 = 0.f, c1 = 0.f, c2 = 0.f, c3 = 0.f, e0 = 0.f, e1 = 0.f, e2 = 0.f, e3 = 0.f;
    for (int gi = 0; gi < ng; gi++) {
      uint32_t a[2], a2[2];
      const uint32_t base = sb + OFF_WF + gi * WF_BYTES + 16384 + i8 * 1024;
      ldsm2t(a, base + (((2 * mt + (mat & 1)) ^ i8) << 4));
      ldsm2t(a2, base + (((2 * mt + 2 + (mat & 1)) ^ i8) << 4));
      const uint32_t hb = lds32(sb + SC_H + gi * 16 + (lane & 3) * 4);
      mma1688(c0, c1, c2, c3, a, hb);
      mma1688(e0, e1, e2, e3, a2, hb);
    }
    const float v = (lane & 2) ? ((lane & 1) ? e2 : e0) : ((lane & 1) ? c2 : c0);
    ll_st(&g_D[b][c][(mt + ((lane >> 1) & 1)) * 16 + g + 8 * (lane & 1)], v, tag);
  }
  hint_arrive(&g_cntD[b], t);
  if (t == 0) stamp2(b + 2 * layer, 7);
  AUX_STAGE();
  if (!last) hint_wait(&g_cntD[b], use * NMAIN - 4 * CFG_HINT_K, t);
  {
    float d0, d1, d2, d3;
    ll_wait4(&g_D[b][t][4 * c], tag, d0, d1, d2, d3);
    __syncwarp();
    const float d = warp_sum4(d0, d1, d2, d3, lane);
    if (i8 == 0) stsf(sb + SC_RED4 + (wq * 4 + mat) * 4, d);
    aux_sync();
    if (wq == 0) {
      const uint32_t e = sb + SC_RED4 + mat * 4;
      const float xres = bf16r(ldsf(sb + OFF_XRES + (b * 4 + mat) * 4) +
                               bf16r((ldsf(e) + ldsf(e + 16)) + (ldsf(e + 32) + ldsf(e + 48))));
      __syncwarp();
      if (i8 == 0) {
        stsf(sb + OFF_XRES + (b * 4 + mat) * 4, xres);
        if (layer == 0) ll_st(&g_X2[b][4 * c + mat], xres, tag);
        else p.out[b * DM + 4 * c + mat] = __float2bfloat16_rn(xres);
      }
    }
    if (layer == 0) hint_arrive(&g_cntX2[b], t);
  }
  if (t == 0) stamp2(b + 2 * layer, 8);
  AUX_STAGE();
  if (layer == 0) {
    {
      float x0, x1, x2, x3;
      hint_wait(&g_cntX2[b], epoch * NMAIN - 4 * CFG_HINT_K, t);
      ll_wait4(&g_X2[b][4 * t], tag, x0, x1, x2, x3);
      if (t == 0) stamp2(b + 2 * layer, 9);
      aux_layernorm(sb, sb + OFF_XN, t, x0, x1, x2, x3);
    }
    AUX_STAGE();
    aux_qproj(sb, t, h, r, sb + OFF_XN, sb + OFF_XN, b, 1, tag);
    AUX_STAGE();
    if (t == 0) stamp2(b + 2 * layer, 10);
    int bq;
    asm volatile("mov.u32 %0, %1;" : "=r"(bq) : "r"(b));
    hint_wait(&g_cntQ[bq][h], epoch * 8 - (CFG_HINT_K ? 1 : 0), t);
    qfrag_store(sb + OFF_QF + b * 256, t, ll_wait1(&g_Q[b][h][t], tag));
    aux_sync();
    if (t == 0) mbar_arrive(sb + (b ? BAR_R1 : BAR_R0));
  }
}

__device__ __forceinline__ void aux_fill_wq(const Params& p, const uint32_t sb, const int t, const int c) {
  const int h = c >> 2, r = c & 3;
#pragma unroll 4
  for (int i = 0; i < 16; i++) {
    const int row = i * 32 + (t >> 2), ch = t & 3;
    cp16(sb + OFF_WQ + row * 64 + ((ch ^ ((row >> 1) & 3)) << 4), p.wq + (size_t)row * (NH * 128) + h * 128 + r * 32 + ch * 8);
  }
}
__device__ __forceinline__ void aux_fill_rest(const Params& p, const uint32_t sb, const int t, const int c) {
  const int h = c >> 2, r = c & 3;
#pragma unroll 1
  for (int i = 0; i < 16; i++) {
    const int row = i * 8 + (t >> 4), ch = t & 15;
    cp16(sb + OFF_WO + row * 256 + ((ch ^ (row & 7)) << 4), p.wo + (size_t)(h * 128 + row) * DM + r * 128 + ch * 8);
    if ((i & 3) == 3) cp_wait_all();
  }
  const int ng = ffn_groups(c);
#pragma unroll 1
  for (int gi = 0; gi < ng; gi++) {
    const int G = gi ? ffn_second(c) : c;
    const uint32_t base = sb + OFF_WF + gi * WF_BYTES;
#pragma unroll 1
    for (int i = 0; i < 4; i++) {
      const int q = i * 128 + t;
      cp16(base + q * 16, p.wg + (size_t)q * FF + G * 8);
      cp16(base + 8192 + q * 16, p.wu + (size_t)q * FF + G * 8);
      const int row = q >> 6, ch = q & 63;
      cp16(base + 16384 + row * 1024 + ((ch ^ row) << 4), p.wd + (size_t)(G * 8 + row) * DM + ch * 8);
      if (i & 1) cp_wait_all();
    }
  }
  aux_sync();
}

__device__ __forceinline__ void aux_init_main(const Params& p, const uint32_t sb, const int t, const int c, const uint32_t tag) {
  const uint2 xa = *reinterpret_cast<const uint2*>(p.x + 4 * t);
  const uint2 xb = *reinterpret_cast<const uint2*>(p.x + DM + 4 * t);
  if (t == 0) stamp2(0, 14);
  aux_layernorm(sb, sb + OFF_XN, t, bflo(xa.x), bfhi(xa.x), bflo(xa.y), bfhi(xa.y));
  aux_layernorm(sb, sb + SC_XN1, t, bflo(xb.x), bfhi(xb.x), bflo(xb.y), bfhi(xb.y));
  cp_wait_all();
  aux_sync();
  if (t == 0) stamp2(1, 14);
  aux_qproj(sb, t, c >> 2, c & 3, sb + OFF_XN, sb + SC_XN1, 0, 2, tag);
  if (t == 0) stamp2(2, 14);
}

__device__ __forceinline__ void aux_main(const Params& p, const uint32_t sb, const int t, const int c, const uint32_t epoch) {
  const int h = c >> 2;
  const uint32_t tag0 = ll_tag(epoch, 0);
  {
    float q0, q1;
    ll_wait2s(&g_Q[0][h][t], NH * 128, tag0, q0, q1);
    qfrag_store(sb + OFF_QF, t, q0);
    qfrag_store(sb + OFF_QF + 256, t, q1);
  }
  aux_sync();
  if (t == 0) mbar_arrive(sb + BAR_Q1);
  if (t == 0) stamp(1);
  aux_fill_rest(p, sb, t, c);
  if (t < 8) stsf(sb + OFF_XRES + t * 4, __bfloat162float(p.x[(t >> 2) * DM + 4 * c + (t & 3)]));
  aux_sync();
#pragma unroll 1
  for (int k = 0; k < 4; k++) {
    const int b = k & 1, layer = k >> 1;
    aux_chain(p, sb, c, b, layer, epoch, k == 3 ? sb + OFF_RING : sb + OFF_PART, k == 3 ? RING_W : 528,
              sb + BAR_P0 + 8 * k);
    if (t == 0) stamp(3 + 2 * k);
  }
}

__device__ __forceinline__ void aux_helper(const uint32_t sb, const int t, const int j, const uint32_t epoch) {
  const uint32_t tag0 = ll_tag(epoch, 0), tag1 = ll_tag(epoch, 1), tag2 = ll_tag(epoch, 2);
  const uint32_t qf = sb + OFF_QF_HELP;
#pragma unroll 1
  for (int w = 0; w < 8; w++) {
    hint_wait(&g_cntQ[1][8 * j + w], epoch * 8 - 4, t);
    for (int b = 0; b < 2; b++) qfrag_store(qf + w * 512 + b * 256, t, ll_wait1(&g_Q[b][8 * j + w][t], tag0));
  }
  aux_sync();
  if (t == 0) mbar_arrive(sb + BAR_Q1);
#pragma unroll 1
  for (int k = 0; k < 4; k++) {
    const int b = k & 1, layer = k >> 1;
    const uint32_t tag = layer ? tag2 : tag1;
    const uint32_t area = k == 3 ? sb + OFF_RING : sb + OFF_PART, astride = k == 3 ? RING_W : 528;
    mbar_wait(sb + BAR_P0 + 8 * k, 0);
    for (int w = 0; w < 8; w++) {
      const float m = ldsf(area + w * astride + 512), mt = ll_trunc(m), sc = ex2(m - mt);
      ll_st(&g_P[b][8 * j + w][4][t], sc * ldsf(area + w * astride + t * 4), tag);
      if (t < 2) ll_st(&g_P[b][8 * j + w][4][128 + t], t ? sc * ldsf(area + w * astride + 516) : mt, tag);
    }
    aux_sync();
    if (t < 8) asm volatile("red.relaxed.gpu.global.add.u32 [%0], 1;" ::"l"(&g_cntP[b][8 * j + t]) : "memory");
    if (layer == 0) {
#pragma unroll 1
      for (int w = 0; w < 8; w++) {
        hint_wait(&g_cntQ[b][8 * j + w], epoch * 8, t);
        qfrag_store(qf + w * 512 + b * 256, t, ll_wait1(&g_Q[b][8 * j + w][t], tag1));
      }
      aux_sync();
      if (t == 0) mbar_arrive(sb + (b ? BAR_R1 : BAR_R0));
    }
  }
}

__global__ void __launch_bounds__(384, 1)
fused_decode_kernel(const __grid_constant__ CUtensorMap tmK, const __grid_constant__ CUtensorMap tmV,
                    const __grid_constant__ Params p) {
  extern __shared__ __align__(1024) uint8_t smem[];
  if (threadIdx.x == 0) stamp(14);
  const uint32_t sb = (uint32_t)__cvta_generic_to_shared(smem);
  const int tid = threadIdx.x;
  const int w = __shfl_sync(0xffffffffu, tid >> 5, 0);
  const int lane = tid & 31;
  const int c = blockIdx.x;
  const bool helper = c >= NMAIN;

  const uint32_t side = sb + (helper ? OFF_W + 4096 : OFF_WF + ffn_groups(c) * WF_BYTES);
  if (w < 8) {
    if (lane == 0) {
      const int h = helper ? (c - NMAIN) * 8 + w : c >> 2, r = helper ? 4 : c & 3;
      const uint32_t q = helper ? p.q >> 3 : p.q;
      uint32_t own[5], total = 0, start = 0;
#pragma unroll
      for (int i = 0; i < 5; i++) {
        const uint32_t slots = (SMEM_BYTES - (OFF_WF + ffn_groups(4 * h + (i & 3)) * WF_BYTES)) >> 12;
        own[i] = i < 4 ? 8 * RP + slots + p.q : (p.ht ? RP + S_HELP_W + (p.q >> 3) : 0);
        if (i < r) start += own[i];
        total += own[i];
      }
      const uint32_t np = TPH - total;
      const uint32_t n1 = TPH - p.ht;
      uint32_t p1o = 0, p1n = 0;
#pragma unroll
      for (int i = 0; i < 5; i++) {
        const uint32_t cnt = i < 4 ? ((n1 + i) >> 2) - own[i] : p.ht - own[4];
        if (i < r) p1o += cnt;
        if (i == r) p1n = cnt;
      }
      const uint32_t h2 = p.ht ? p.h2 + (h < 12 ? 6 : 0) : 0, n2 = np - h2;
      const uint32_t p2n = helper ? h2 : (n2 + r) >> 2;
      uint32_t p2o = 0;
#pragma unroll
      for (int i = 0; i < 4; i++) if (i < r) p2o += (n2 + i) >> 2;
      const uint32_t hb = h * TPH, base = hb + start, zone = hb + total;
      uint32_t ctr, qf, st0, pk, rt, keep;
      if (!helper) {
        const uint32_t ns = (sb + SMEM_BYTES - side) >> 12;
        rt = base + w * RP;
        st0 = base + 8 * RP + w;
        pk = w | (8u << 8) | (8u << 16) | (((ns - w + 7) >> 3) << 24);
        keep = base + 8 * RP + ns;
        ctr = sb + OFF_CTR;
        qf = sb + OFF_QF;
      } else {
        rt = base;
        st0 = base + RP;
        pk = (w * S_HELP_W) | (1u << 8) | (1u << 16) | ((uint32_t)S_HELP_W << 24);
        keep = base + RP + S_HELP_W;
        ctr = sb + OFF_CTR + w * 4;
        qf = sb + OFF_QF_HELP + w * 512;
      }
      const uint32_t wp = sb + OFF_WP + w * 32;
      const uint32_t seg = helper ? side + 8 * S_HELP_W * 4096 + w * 128 : sb + OFF_SEG;
      sts32(wp, seg); sts32(wp + 4, ctr);
      sts32(wp + 16, qf); sts32(wp + 20, st0); sts32(wp + 24, pk); sts32(wp + 28, rt);
      if (helper || w == 0) {
        auto blk = [&](int i, uint32_t lim, uint32_t base_d, uint32_t pf, uint32_t cnt) {
          sts32(seg + i * 16, lim); sts32(seg + i * 16 + 4, base_d); sts32(seg + i * 16 + 8, pf); sts32(seg + i * 16 + 12, cnt);
        };
        const uint32_t t0 = p1n, t1 = t0 + q, t2 = t1 + p1n, t3 = t2 + q, t4 = t3 + p2n, t5 = t4 + p2n;
        blk(0, t0, (D_VALID | D_B0) + zone + p1o, 0xffffffffu, 0);
        blk(1, t1, (D_VALID | D_B0) + keep - t0, 0, 0);
        blk(2, t2, (D_VALID | D_B1 | D_PAST0) + zone + p1o + TPB - t1, 0xffffffffu, 0);
        blk(3, t3, (D_VALID | D_B1 | D_PAST0) + keep + TPB - t2, 0, 0);
        blk(4, t4, (D_VALID | D_B0 | D_N0 | D_PAST0 | D_PAST1) + zone + p2o - t3, 0xffffffffu, 0);
        blk(5, t5, (D_VALID | D_B1 | D_N1 | D_PASTS) + zone + p2o + (helper ? 0 : 0) + TPB - t4, 0xffffffffu, 0);
        blk(6, 0, 0, 0xffffffffu, 0);
        blk(7, q, keep + q - 1, 0, ctr + 32);
      }
      for (int s = 0; s < 4; s++) mbar_init(sb + OFF_RBAR + (w * 4 + s) * 8, 1);
      for (int s = w; s < 40; s += 8) mbar_init(sb + OFF_SBAR + s * 8, 1);
    }
  } else {
    if (!helper) aux_fill_wq(p, sb, tid - 256, c);
    if (w == 8) {
      if (lane < 24) sts32(sb + OFF_CTR + lane * 4, 0);
      if (lane == 0) {
        mbar_init(sb + BAR_Q1, 1); mbar_init(sb + BAR_R0, 1); mbar_init(sb + BAR_R1, 1);
        for (int k = 0; k < 4; k++) mbar_init(sb + BAR_P0 + 8 * k, 8);
      }
    }
  }
  asm volatile("fence.mbarrier_init.release.cluster;" ::: "memory");
  asm volatile("fence.proxy.async.shared::cta;" ::: "memory");
  __syncthreads();
  if (tid == 0) stamp(0);

  if (w < 8) {
    stream_prologue(&tmK, &tmV, sb, side, w, lane);
    asm volatile("setmaxnreg.inc.sync.aligned.u32 %0;" ::"n"(CFG_REG_S));
    int lane2;
    asm volatile("mov.u32 %0, %%laneid;" : "=r"(lane2));
    stream_warp(&tmK, &tmV, sb, side, w, lane2, p);
  } else {
    uint32_t epoch;
    asm volatile("ld.relaxed.gpu.global.u32 %0, [%1];" : "=r"(epoch) : "l"(&g_epoch) : "memory");
    epoch += 1;
    if (!helper) aux_init_main(p, sb, tid - 256, c, ll_tag(epoch, 0));
    asm volatile("setmaxnreg.dec.sync.aligned.u32 %0;" ::"n"(CFG_REG_A));
    int t;
    asm volatile("mov.u32 %0, %%tid.x;" : "=r"(t));
    t -= 256;
    if (!helper) aux_main(p, sb, t, c, epoch);
    else aux_helper(sb, t, c - NMAIN, epoch);
    if (c == 0 && t == 0) asm volatile("st.relaxed.gpu.global.u32 [%0], %1;" ::"l"(&g_epoch), "r"(epoch) : "memory");
    if (t == 0) stamp(13);
  }
}

typedef CUresult (*EncodeTiledFn)(CUtensorMap*, CUtensorMapDataType, cuuint32_t, void*, const cuuint64_t*,
                                  const cuuint64_t*, const cuuint32_t*, const cuuint32_t*, CUtensorMapInterleave,
                                  CUtensorMapSwizzle, CUtensorMapL2promotion, CUtensorMapFloatOOBfill);

}

extern "C" void kernel_launch(void* const* d_in, const int* in_sizes, int n_in, void* d_out, int out_size) {
  (void)in_sizes; (void)n_in; (void)out_size;
  static EncodeTiledFn encode = nullptr;
  static int sms = 0;
  if (!encode) {
    void* fn = nullptr;
    cudaDriverEntryPointQueryResult qr;
    cudaGetDriverEntryPoint("cuTensorMapEncodeTiled", &fn, cudaEnableDefault, &qr);
    encode = (EncodeTiledFn)fn;
    int dev = 0;
    cudaGetDevice(&dev);
    cudaDeviceGetAttribute(&sms, cudaDevAttrMultiProcessorCount, dev);
    cudaFuncSetAttribute(fused_decode_kernel, cudaFuncAttributeMaxDynamicSharedMemorySize, SMEM_BYTES);
  }
  CUtensorMap tmK, tmV;
  const cuuint64_t gdim[2] = {64, (cuuint64_t)2 * NH * SK * 2};
  const cuuint64_t gstr[1] = {128};
  const cuuint32_t box[2] = {64, 16};
  const cuuint32_t estr[2] = {1, 1};
  encode(&tmK, CU_TENSOR_MAP_DATA_TYPE_BFLOAT16, 2, d_in[1], gdim, gstr, box, estr, CU_TENSOR_MAP_INTERLEAVE_NONE,
         CU_TENSOR_MAP_SWIZZLE_128B, CU_TENSOR_MAP_L2_PROMOTION_NONE, CU_TENSOR_MAP_FLOAT_OOB_FILL_NONE);
  encode(&tmV, CU_TENSOR_MAP_DATA_TYPE_BFLOAT16, 2, d_in[2], gdim, gstr, box, estr, CU_TENSOR_MAP_INTERLEAVE_NONE,
         CU_TENSOR_MAP_SWIZZLE_128B, CU_TENSOR_MAP_L2_PROMOTION_NONE, CU_TENSOR_MAP_FLOAT_OOB_FILL_NONE);
  Params p;
  p.x = (const __nv_bfloat16*)d_in[0];
  p.wq = (const __nv_bfloat16*)d_in[3];
  p.wo = (const __nv_bfloat16*)d_in[4];
  p.wg = (const __nv_bfloat16*)d_in[6];
  p.wu = (const __nv_bfloat16*)d_in[7];
  p.wd = (const __nv_bfloat16*)d_in[8];
  p.out = (__nv_bfloat16*)d_out;
  const bool helpers = sms >= NMAIN + NHELP;
  p.ht = helpers ? CFG_HT : 0;
  p.h2 = CFG_H2;
  p.q = CFG_Q;
  p.zero = 0;
  p.kbytes = (const uint8_t*)d_in[1];
  p.vbytes = (const uint8_t*)d_in[2];
  fused_decode_kernel<<<helpers ? NMAIN + NHELP : NMAIN, 384, SMEM_BYTES, cudaStreamPerThread>>>(tmK, tmV, p);
}
```

```cpp
#include <cuda_runtime.h>
#include <cuda_bf16.h>
#include <cuda.h>
#include <stdint.h>

namespace {

constexpr int DM = 512;
constexpr int NH = 32;
constexpr int SK = 16384;
constexpr int FF = 1376;
constexpr int TPH = SK / 8;
constexpr int TPB = NH * TPH;

#define CFG_RP 6
#define CFG_REG_S 232
#define CFG_REG_A 40
#define CFG_Q 144
#define CFG_IDLE 0
#define CFG_IDLE_WAIT 0
#define CFG_HINT_SLEEP 20
#define CFG_PFDELAY 0
#define CFG_RING_PRIO 0
#define CFG_SIDE_EVERY 1
#define CFG_HINT_K 0
#define CFG_SLOTS 3
#define CFG_SIDE_MAX 1
#define CFG_H2 30
#define CFG_HT 56
constexpr int RP = CFG_RP;
constexpr int NMAIN = 128;
constexpr int NHELP = 4;
constexpr int S_HELP_W = CFG_SLOTS == 3 ? 5 : 4;
constexpr int NGRP = FF / 8;
static_assert(NGRP - NMAIN == NH + 12, "second ffn groups: quarter 0 of every head, quarter 1 of the first 12 heads");
__host__ __device__ constexpr int ffn_groups(int c) { return ((c & 3) == 0 || ((c & 3) == 1 && (c >> 2) < 12)) ? 2 : 1; }
__host__ __device__ constexpr int ffn_second(int c) { return NMAIN + (c >> 2) + ((c & 3) ? NH : 0); }

constexpr uint32_t SMEM_BYTES = 232448;
constexpr uint32_t OFF_RING = 0;
constexpr uint32_t RING_W = CFG_SLOTS * 2048;
constexpr uint32_t OFF_MISC = 8 * RING_W;
constexpr uint32_t OFF_RBAR = OFF_MISC;
constexpr uint32_t OFF_SBAR = OFF_RBAR + 32 * 8;
constexpr uint32_t OFF_CBAR = OFF_SBAR + 40 * 8;
constexpr uint32_t BAR_Q1 = OFF_CBAR + 0, BAR_R0 = OFF_CBAR + 8, BAR_R1 = OFF_CBAR + 16;
constexpr uint32_t BAR_P0 = OFF_CBAR + 24;
constexpr uint32_t OFF_CTR = OFF_CBAR + 56;
constexpr uint32_t OFF_HELD = OFF_CTR + 96;
constexpr uint32_t OFF_WP = OFF_MISC + 768;
constexpr uint32_t OFF_QF = OFF_WP + 256;
constexpr uint32_t OFF_PART = OFF_QF + 512;
constexpr uint32_t OFF_XN = OFF_PART + 8 * 132 * 4;
constexpr uint32_t OFF_RED = OFF_XN + 1024;
constexpr uint32_t OFF_XRES = OFF_RED + 32;
constexpr uint32_t OFF_SEG = OFF_RED + 64;
constexpr uint32_t OFF_W = OFF_MISC + 7168;
constexpr uint32_t OFF_WQ = OFF_W;
constexpr uint32_t OFF_WO = OFF_WQ + 32768;
constexpr uint32_t OFF_WD = OFF_WO + 32768;
constexpr uint32_t OFF_WF = OFF_WD + 11264;
constexpr uint32_t WF_BYTES = 16384;
constexpr uint32_t OFF_QF_HELP = OFF_W;
static_assert(OFF_HELD + 32 <= OFF_WP, "smem map");
static_assert(OFF_SEG + 128 <= OFF_W && OFF_W % 1024 == 0 && OFF_WF % 1024 == 0, "smem map");
constexpr uint32_t SC_RED4 = OFF_PART;
constexpr uint32_t SC_XN1 = OFF_PART + 1024;
constexpr uint32_t SC_O = OFF_PART + 2048;

__device__ __align__(16) uint32_t g_P[2][NH][5][132];
__device__ __align__(16) uint32_t g_Z[2][NH][DM];
__device__ __align__(16) uint32_t g_X1[2][DM];
__device__ __align__(16) uint32_t g_H[2][FF];
__device__ __align__(16) uint32_t g_X2[2][DM];
__device__ __align__(16) uint32_t g_Q[2][NH][128];
__device__ unsigned int g_epoch;
__device__ unsigned int g_cntP[2][NH], g_cntQ[2][NH], g_cntZ[2][4], g_cntX1[2], g_cntD[2], g_cntX2[2];

struct Params {
  const __nv_bfloat16* x;
  const __nv_bfloat16* wq;
  const __nv_bfloat16* wo;
  const __nv_bfloat16* wg;
  const __nv_bfloat16* wu;
  const __nv_bfloat16* wd;
  __nv_bfloat16* out;
  int ht;
  int h2;
  int q;
  uint32_t zero;
  const uint8_t* kbytes;
  const uint8_t* vbytes;
};

constexpr uint32_t D_TILE = 0x1FFFFu;
constexpr uint32_t D_B0 = 1u << 17, D_B1 = 1u << 18;
constexpr uint32_t D_N0 = 1u << 19, D_N1 = 1u << 20;
constexpr uint32_t D_PF = 1u << 21;
constexpr uint32_t D_REG = 1u << 22;
constexpr uint32_t D_PAST0 = 1u << 23, D_PAST1 = 1u << 24, D_PAST2 = 1u << 25;
constexpr uint32_t D_VALID = 1u << 26, D_END = 1u << 27;
constexpr uint32_t D_PASTS = D_PAST0 | D_PAST1 | D_PAST2;
constexpr uint32_t ST_R0 = 1u << 0, ST_R1 = 1u << 1, ST_INJ = 1u << 2, ST_INJ2 = 1u << 3, ST_FL0 = 1u << 7,
                   ST_FL1 = 1u << 8, ST_FL2 = 1u << 9, ST_REGC = 1u << 10, ST_CURB = 1u << 11,
                   ST_SONLY = 1u << 12;
constexpr int SH_SKIP = 13;
constexpr int SS_F = 0, SS_H0 = 5, SS_H1 = 10, SS_B = 15, SS_K = 20, SS_P = 25;

constexpr uint64_t POL_FIRST = 0x12F0000000000000ull;
constexpr uint64_t POL_NORMAL = 0x16F0000000000000ull;
constexpr float SCALE_LOG2 = 0.08838834764831845f * 1.4426950408889634f;
constexpr int SPIN_LIMIT = 1 << 22;

__device__ __forceinline__ void mbar_init(uint32_t bar, uint32_t cnt) {
  asm volatile("mbarrier.init.shared::cta.b64 [%0], %1;" ::"r"(bar), "r"(cnt) : "memory");
}
__device__ __forceinline__ void mbar_expect_tx(uint32_t bar, uint32_t bytes) {
  asm volatile("mbarrier.arrive.expect_tx.shared::cta.b64 _, [%0], %1;" ::"r"(bar), "r"(bytes) : "memory");
}
__device__ __forceinline__ void mbar_arrive(uint32_t bar) {
  asm volatile("mbarrier.arrive.shared::cta.b64 _, [%0];" ::"r"(bar) : "memory");
}
__device__ __forceinline__ bool mbar_test(uint32_t bar, uint32_t parity) {
  uint32_t ok;
  asm volatile("{\n.reg .pred p;\nmbarrier.test_wait.parity.shared::cta.b64 p, [%1], %2;\nselp.u32 %0, 1, 0, p;\n}"
               : "=r"(ok) : "r"(bar), "r"(parity) : "memory");
  return ok != 0;
}
__device__ __forceinline__ bool mbar_try(uint32_t bar, uint32_t parity) {
  uint32_t ok;
  asm volatile("{\n.reg .pred p;\nmbarrier.try_wait.parity.shared::cta.b64 p, [%1], %2;\nselp.u32 %0, 1, 0, p;\n}"
               : "=r"(ok) : "r"(bar), "r"(parity) : "memory");
  return ok != 0;
}
__device__ __forceinline__ void mbar_wait(uint32_t bar, uint32_t parity) {
  int it = 0;
  while (!__all_sync(0xffffffffu, mbar_try(bar, parity)))
    if (++it > SPIN_LIMIT) __trap();
}
__device__ __forceinline__ void tma_load(uint32_t dst, const CUtensorMap* tm, int c0, int row, uint32_t bar) {
  asm volatile(
      "cp.async.bulk.tensor.2d.shared::cluster.global.tile.mbarrier::complete_tx::bytes.L2::cache_hint"
      " [%0], [%1, {%2, %3}], [%4], %5;" ::"r"(dst), "l"(tm), "r"(c0), "r"(row), "r"(bar), "l"(POL_FIRST)
      : "memory");
}
__device__ __forceinline__ void ldsm4(uint32_t* r, uint32_t addr) {
  asm volatile("ldmatrix.sync.aligned.m8n8.x4.shared.b16 {%0,%1,%2,%3}, [%4];"
               : "=r"(r[0]), "=r"(r[1]), "=r"(r[2]), "=r"(r[3]) : "r"(addr) : "memory");
}
__device__ __forceinline__ void ldsm4t(uint32_t* r, uint32_t addr) {
  asm volatile("ldmatrix.sync.aligned.m8n8.x4.trans.shared.b16 {%0,%1,%2,%3}, [%4];"
               : "=r"(r[0]), "=r"(r[1]), "=r"(r[2]), "=r"(r[3]) : "r"(addr) : "memory");
}
__device__ __forceinline__ void mma16816(float& d0, float& d1, float& d2, float& d3, const uint32_t* a, uint32_t b0,
                                         uint32_t b1) {
  asm("mma.sync.aligned.m16n8k16.row.col.f32.bf16.bf16.f32 {%0,%1,%2,%3}, {%4,%5,%6,%7}, {%8,%9}, {%0,%1,%2,%3};"
      : "+f"(d0), "+f"(d1), "+f"(d2), "+f"(d3)
      : "r"(a[0]), "r"(a[1]), "r"(a[2]), "r"(a[3]), "r"(b0), "r"(b1));
}
__device__ __forceinline__ void mma16816v(float& d0, float& d1, float& d2, float& d3, const uint32_t* a, uint32_t b0,
                                          uint32_t b1) {
  asm volatile("mma.sync.aligned.m16n8k16.row.col.f32.bf16.bf16.f32 {%0,%1,%2,%3}, {%4,%5,%6,%7}, {%8,%9}, {%0,%1,%2,%3};"
               : "+f"(d0), "+f"(d1), "+f"(d2), "+f"(d3)
               : "r"(a[0]), "r"(a[1]), "r"(a[2]), "r"(a[3]), "r"(b0), "r"(b1));
}
__device__ __forceinline__ uint32_t lds32(uint32_t a) {
  uint32_t v;
  asm volatile("ld.shared.u32 %0, [%1];" : "=r"(v) : "r"(a) : "memory");
  return v;
}
__device__ __forceinline__ uint2 lds64(uint32_t a) {
  uint2 v;
  asm volatile("ld.shared.v2.u32 {%0,%1}, [%2];" : "=r"(v.x), "=r"(v.y) : "r"(a) : "memory");
  return v;
}
__device__ __forceinline__ uint4 lds128(uint32_t a) {
  uint4 v;
  asm volatile("ld.shared.v4.u32 {%0,%1,%2,%3}, [%4];" : "=r"(v.x), "=r"(v.y), "=r"(v.z), "=r"(v.w) : "r"(a) : "memory");
  return v;
}
__device__ __forceinline__ float ldsf(uint32_t a) {
  float v;
  asm volatile("ld.shared.f32 %0, [%1];" : "=f"(v) : "r"(a) : "memory");
  return v;
}
__device__ __forceinline__ void stsf(uint32_t a, float v) {
  asm volatile("st.shared.f32 [%0], %1;" ::"r"(a), "f"(v) : "memory");
}
__device__ __forceinline__ void sts32(uint32_t a, uint32_t v) {
  asm volatile("st.shared.u32 [%0], %1;" ::"r"(a), "r"(v) : "memory");
}
__device__ __forceinline__ void sts16(uint32_t a, uint16_t v) {
  asm volatile("st.shared.u16 [%0], %1;" ::"r"(a), "h"(v) : "memory");
}
__device__ __forceinline__ float fsqrt_approx(float x) {
  float y;
  asm("sqrt.approx.f32 %0, %1;" : "=f"(y) : "f"(x));
  return y;
}
__device__ __forceinline__ float ex2(float x) {
  float y;
  asm("ex2.approx.ftz.f32 %0, %1;" : "=f"(y) : "f"(x));
  return y;
}
__device__ __forceinline__ int dep_zero(uint32_t r, uint32_t zero) { return (int)(r & zero); }
__device__ __forceinline__ void tma_issue(uint32_t dst, const CUtensorMap* tm, int c0, int row, uint32_t bar) {
  asm volatile(
      "{\n.reg .pred P;\nelect.sync _|P, 0xffffffff;\n"
      "@P mbarrier.arrive.expect_tx.shared::cta.b64 _, [%4], 2048;\n"
      "@P cp.async.bulk.tensor.2d.shared::cluster.global.tile.mbarrier::complete_tx::bytes.L2::cache_hint"
      " [%0], [%1, {%2, %3}], [%4], %5;\n}" ::"r"(dst), "l"(tm), "r"(c0), "r"(row), "r"(bar), "l"(POL_FIRST)
      : "memory");
}
__device__ __forceinline__ void tma_keep(const uint8_t* base, int row) {
  asm volatile(
      "{\n.reg .pred P;\nelect.sync _|P, 0xffffffff;\n"
      "@P cp.async.bulk.prefetch.L2.global.L2::cache_hint [%0], 2048, %1;\n}" ::"l"(base + (size_t)(uint32_t)row * 128),
      "l"(POL_NORMAL)
      : "memory");
}
__device__ __forceinline__ void tma_issue2(uint32_t dst, const CUtensorMap* tmK, const CUtensorMap* tmV, int c0, int row,
                                           uint32_t bar) {
  asm volatile(
      "{\n.reg .pred P;\nelect.sync _|P, 0xffffffff;\n"
      "@P mbarrier.arrive.expect_tx.shared::cta.b64 _, [%5], 4096;\n"
      "@P cp.async.bulk.tensor.2d.shared::cluster.global.tile.mbarrier::complete_tx::bytes.L2::cache_hint"
      " [%0], [%1, {%3, %4}], [%5], %6;\n"
      "@P cp.async.bulk.tensor.2d.shared::cluster.global.tile.mbarrier::complete_tx::bytes.L2::cache_hint"
      " [%7], [%2, {%3, %4}], [%5], %6;\n}" ::"r"(dst), "l"(tmK), "l"(tmV), "r"(c0), "r"(row), "r"(bar), "l"(POL_FIRST),
      "r"(dst + 2048)
      : "memory");
}
__device__ __forceinline__ uint32_t uni(uint32_t v) { return __shfl_sync(0xffffffffu, v, 0); }
__device__ __forceinline__ uint32_t ticket_take(uint32_t addr) {
  uint32_t v = 0;
  asm volatile("{\n.reg .pred P;\nelect.sync _|P, 0xffffffff;\n@P atom.shared.add.u32 %0, [%1], 1;\n}"
               : "+r"(v) : "r"(addr) : "memory");
  return v;
}
__device__ __forceinline__ uint32_t ticket_bcast(uint32_t v) { return __reduce_max_sync(0xffffffffu, v); }
__device__ __forceinline__ uint32_t pack_bf16(float lo, float hi) {
  uint32_t r;
  asm("cvt.rn.bf16x2.f32 %0, %1, %2;" : "=r"(r) : "f"(hi), "f"(lo));
  return r;
}
__device__ __forceinline__ float bf16r(float x) { return __uint_as_float(pack_bf16(0.f, x) & 0xffff0000u); }
__device__ __forceinline__ float bflo(uint32_t w) { return __uint_as_float(w << 16); }
__device__ __forceinline__ float bfhi(uint32_t w) { return __uint_as_float(w & 0xffff0000u); }

__device__ __forceinline__ uint32_t ll_tag(uint32_t epoch, uint32_t stage) { return 1 + (epoch * 3 + stage) % 255; }
__device__ __forceinline__ float ll_trunc(float v) { return __uint_as_float(__float_as_uint(v) & 0xffffff00u); }
__device__ __forceinline__ void ll_st(uint32_t* p, float v, uint32_t tag) {
  asm volatile("st.relaxed.gpu.global.u32 [%0], %1;" ::"l"(p), "r"((__float_as_uint(v) & 0xffffff00u) | tag) : "memory");
}
__device__ __forceinline__ void aux_sync() { asm volatile("bar.sync 1, 128;" ::: "memory"); }
__device__ __forceinline__ void stamp(int) {}
__device__ __forceinline__ void stamp2(int, int) {}

struct Acc { float o0, o1, o2, o3, m, l; };

__device__ __forceinline__ uint32_t softmax8(float s0, float s1, float s2, float s3, Acc& a, int lane) {
  const float sc = ((lane & 16) ? (s1 + s2) : (s0 + s3)) * SCALE_LOG2;
  if (__any_sync(0xffffffffu, sc > a.m)) {
    float mx = fmaxf(sc, __shfl_xor_sync(0xffffffffu, sc, 4));
    mx = fmaxf(mx, __shfl_xor_sync(0xffffffffu, mx, 8));
    mx = fmaxf(mx, __shfl_xor_sync(0xffffffffu, mx, 16));
    mx = fmaxf(mx, a.m);
    const float alpha = ex2(a.m - mx);
    a.o0 *= alpha; a.o1 *= alpha; a.o2 *= alpha; a.o3 *= alpha; a.l *= alpha;
    a.m = mx;
  }
  const float p = ex2(sc - a.m);
  a.l += p;
  uint32_t pp, pk;
  asm("cvt.rn.bf16x2.f32 %0, %1, %1;" : "=r"(pp) : "f"(p));
  asm volatile("movmatrix.sync.aligned.m8n8.trans.b16 %0, %1;" : "=r"(pk) : "r"(pp));
  return pk;
}
__device__ __forceinline__ uint32_t qk_reg(const uint32_t* kf, uint32_t qaddr, Acc& a, int lane) {
  float s0 = 0.f, s1 = 0.f, s2 = 0.f, s3 = 0.f;
  {
    const uint4 q = lds128(qaddr);
    mma16816(s0, s1, s2, s3, kf + 0, q.x, q.y);
    mma16816(s0, s1, s2, s3, kf + 4, q.z, q.w);
  }
  {
    const uint4 q = lds128(qaddr + 128);
    mma16816(s0, s1, s2, s3, kf + 8, q.x, q.y);
    mma16816(s0, s1, s2, s3, kf + 12, q.z, q.w);
  }
  return softmax8(s0, s1, s2, s3, a, lane);
}
__device__ __forceinline__ void pv_q(const uint32_t* vf, int j, uint32_t pk, Acc& a, int lane) {
  const int g = lane >> 2;
  const bool cm = ((g & 1) == 0) == ((lane & 2) == 0);
  const bool mine = (g >> 1) == j;
  mma16816(a.o0, a.o1, a.o2, a.o3, vf, (mine && cm) ? pk : 0u, (mine && !cm) ? pk : 0u);
}
__device__ __forceinline__ void pv_reg(const uint32_t* vf, uint32_t pk, Acc& a, int lane) {
#pragma unroll
  for (int j = 0; j < 4; j++) pv_q(vf + 4 * j, j, pk, a, lane);
}

__device__ __forceinline__ void side_fill_w(const CUtensorMap* tmK, const CUtensorMap* tmV, uint32_t sb, uint32_t side,
                                            uint32_t wp, int lane, uint32_t i, uint32_t b, int dep) {
  const uint4 p = lds128(wp + 16);
  const uint32_t slot = uni((p.z & 255) + i * ((p.z >> 8) & 255));
  const int row = (int)(p.y + i * ((p.z >> 16) & 255) + b * TPB) * 16;
  tma_issue2(side + slot * 4096, tmK, tmV, dep, row, sb + OFF_SBAR + slot * 8);
}
__device__ __forceinline__ void stream_prologue(const CUtensorMap* tmK, const CUtensorMap* tmV, const uint32_t sb,
                                                const uint32_t side, const int w, const int lane) {
  const uint32_t ring = sb + OFF_RING + w * RING_W;
  const uint32_t rbar = sb + OFF_RBAR + w * 32;
  const uint32_t wp = sb + OFF_WP + w * 32;
  const uint4 p = lds128(wp + 16);
  const uint32_t nside = p.z >> 24;
  if (lane == 0) {
    mbar_expect_tx(rbar, 2048);      tma_load(ring, tmK, 0, (int)p.w * 16, rbar);
    mbar_expect_tx(rbar + 8, 2048);  tma_load(ring + 2048, tmV, 0, (int)p.w * 16, rbar + 8);
    mbar_expect_tx(rbar + 16, 2048); tma_load(ring + 4096, tmK, 0, (int)(p.w + 1) * 16, rbar + 16);
    if (CFG_SLOTS == 4) { mbar_expect_tx(rbar + 24, 2048); tma_load(ring + 6144, tmV, 0, (int)(p.w + 1) * 16, rbar + 24); }
  }
  __syncwarp();
  side_fill_w(tmK, tmV, sb, side, wp, lane, 0, 0, 0);
  uint32_t sis = 1;
  if (nside > 1) side_fill_w(tmK, tmV, sb, side, wp, lane, sis++, 0, 0);
  int it = 0;
  while (!__all_sync(0xffffffffu, mbar_test(sb + BAR_Q1, 0))) {
    if (sis < nside &&
        __all_sync(0xffffffffu, mbar_test(sb + OFF_SBAR + ((p.z & 255) + (sis - 2) * ((p.z >> 8) & 255)) * 8, 0)))
      side_fill_w(tmK, tmV, sb, side, wp, lane, sis++, 0, 0);
    else
      __nanosleep(40);
    if (++it > SPIN_LIMIT) __trap();
  }
  if (lane == 0) sts32(sb + OFF_HELD + w * 4, sis);
  __syncwarp();
}

__device__ __forceinline__ void stream_warp(const CUtensorMap* tmK, const CUtensorMap* tmV, const uint32_t sb,
                                            const uint32_t side, const int w, const int lane, const Params& prm) {
  const uint32_t& zero = prm.zero;
  const uint32_t ring = sb + OFF_RING + w * RING_W;
  const uint32_t rbar = sb + OFF_RBAR + w * 32;
  const uint32_t wp = sb + OFF_WP + w * 32;
  uint32_t laneK, laneV;
  {
    const int mat = lane >> 3, i = lane & 7;
    const int hk = (mat & 1) ? (i < 4) : (i >= 4);
    const int rk = 2 * i + hk;
    laneK = ring + rk * 128 + (((mat >> 1) ^ (rk & 7)) << 4);
    laneV = laneK ^ (((mat ^ (mat >> 1)) & 1) << 7);
  }
  const uint32_t qoff = lds128(wp + 16).x + (((lane >> 2) & 1) * 4 + (lane & 3)) * 16;

  uint32_t kv[RP][32];
  Acc cur, oth;
  cur.o0 = cur.o1 = cur.o2 = cur.o3 = cur.l = 0.f; cur.m = -INFINITY;
  oth = cur;
  uint32_t st = 0;
  uint32_t csp = 0;
  uint32_t d0, d1;
  uint32_t ev;
  uint32_t ss = 0;
  uint32_t mseg = lds32(wp);
  const uint32_t ctrM = lds32(wp + 4);
  uint32_t tn = ticket_take(ctrM);

  auto ensure = [&](uint32_t b) {
    const uint32_t sw = b ^ ((st >> 11) & 1);
    static_assert(ST_CURB == 1u << 11, "");
    asm volatile(
        "{\n.reg .pred p;\n.reg .f32 t;\nsetp.eq.u32 p, %12, 0;\n@p bra.uni SKIP;\n"
        "mov.f32 t, %0;\nmov.f32 %0, %6;\nmov.f32 %6, t;\nmov.f32 t, %1;\nmov.f32 %1, %7;\nmov.f32 %7, t;\n"
        "mov.f32 t, %2;\nmov.f32 %2, %8;\nmov.f32 %8, t;\nmov.f32 t, %3;\nmov.f32 %3, %9;\nmov.f32 %9, t;\n"
        "mov.f32 t, %4;\nmov.f32 %4, %10;\nmov.f32 %10, t;\nmov.f32 t, %5;\nmov.f32 %5, %11;\nmov.f32 %11, t;\n"
        "SKIP:\n}"
        : "+f"(cur.o0), "+f"(cur.o1), "+f"(cur.o2), "+f"(cur.o3), "+f"(cur.m), "+f"(cur.l), "+f"(oth.o0), "+f"(oth.o1),
          "+f"(oth.o2), "+f"(oth.o3), "+f"(oth.m), "+f"(oth.l)
        : "r"(sw));
    st ^= sw << 11;
  };
  auto gate = [&](uint32_t b) {
    const uint32_t bit = b ? ST_R1 : ST_R0;
    if (!(st & bit)) { mbar_wait(sb + (b ? BAR_R1 : BAR_R0), 0); st |= bit; }
  };
  auto issue = [&](const CUtensorMap* tm, uint32_t dst, uint32_t bar, uint32_t d, int dep) {
    const int row = (int)(d & D_TILE) * 16;
    tma_issue(dst, tm, dep, row, bar);
    if (CFG_PFDELAY == 0 && (d & D_PF)) tma_keep(tm == tmK ? prm.kbytes : prm.vbytes, row);
  };
  auto keep_late = [&](const uint8_t* base, uint32_t d) {
    if (d & D_PF) tma_keep(base, (int)(d & D_TILE) * 16);
  };
  auto advance = [&]() {
    csp += 2048;
    if ((csp & 0x1800) == 0x1800) csp = (csp & 1) ^ 1;
  };
  auto reg_desc = [&](uint32_t i) { return D_VALID | D_REG | D_B1 | D_PAST0 | (lds128(wp + 16).w + TPB + i); };
  auto grab = [&]() -> uint32_t {
    const uint4 P = lds128(mseg);
    const uint32_t t = ticket_bcast(tn);
    uint32_t d;
    bool held = false;
    if (t < P.x) {
      d = P.y + t;
      if (t >= P.z) d |= D_PF;
    } else {
      const uint32_t s0 = lds32(wp);
      while (true) {
        const uint32_t si = (mseg - s0) >> 4;
        if (si >= 6) { d = D_PASTS | D_END; break; }
        const uint4 M = lds128(mseg);
        if (t < M.x) { d = (M.y + t) | (t >= M.z ? D_PF : 0u); break; }
        if (si == 3 && !(st & ST_INJ)) {
          st = (st | ST_INJ | ST_INJ2) & ~ST_SONLY;
          ev |= D_VALID;
          held = true;
          d = reg_desc(0);
          break;
        }
        mseg += 16;
      }
    }
    if (held) tn = t; else tn = ticket_take(ctrM);
    return d;
  };
  auto qk_smem = [&](Acc& A, uint32_t la, uint32_t qa, auto mid) -> uint32_t {
    float s0 = 0.f, s1 = 0.f, s2 = 0.f, s3 = 0.f;
    uint32_t f[8];
    ldsm4(f, la); ldsm4(f + 4, la ^ 32);
    {
      const uint4 q = lds128(qa);
      mma16816v(s0, s1, s2, s3, f, q.x, q.y);
      mma16816v(s0, s1, s2, s3, f + 4, q.z, q.w);
    }
    ldsm4(f, la ^ 64); ldsm4(f + 4, la ^ 96);
    mid(f[7]);
    {
      const uint4 q = lds128(qa + 128);
      mma16816v(s0, s1, s2, s3, f, q.x, q.y);
      mma16816v(s0, s1, s2, s3, f + 4, q.z, q.w);
    }
    return softmax8(s0, s1, s2, s3, A, lane);
  };
  auto pv_smem = [&](Acc& A, uint32_t la, uint32_t pk, auto mid) {
    const int g = lane >> 2;
    const bool cm = ((g & 1) == 0) == ((lane & 2) == 0);
    const uint32_t b0 = cm ? pk : 0u, b1 = cm ? 0u : pk;
    uint32_t f[8];
    ldsm4t(f, la); ldsm4t(f + 4, la ^ 32);
    mma16816v(A.o0, A.o1, A.o2, A.o3, f, (g >> 1) == 0 ? b0 : 0u, (g >> 1) == 0 ? b1 : 0u);
    mma16816v(A.o0, A.o1, A.o2, A.o3, f + 4, (g >> 1) == 1 ? b0 : 0u, (g >> 1) == 1 ? b1 : 0u);
    ldsm4t(f, la ^ 64); ldsm4t(f + 4, la ^ 96);
    mid(f[7]);
    mma16816v(A.o0, A.o1, A.o2, A.o3, f, (g >> 1) == 2 ? b0 : 0u, (g >> 1) == 2 ? b1 : 0u);
    mma16816v(A.o0, A.o1, A.o2, A.o3, f + 4, (g >> 1) == 3 ? b0 : 0u, (g >> 1) == 3 ? b1 : 0u);
  };
#define LOG_STEP(kind)
  auto ring_step = [&](const uint32_t d2) {
    csp = uni(csp);
    uint32_t so = csp & 0x1800, bar = rbar + (csp >> 8);
    mbar_wait(bar, csp & 1);
    const uint32_t pk = qk_smem(cur, laneK + so, qoff + ((d0 >> 8) & 256), [&](uint32_t last) {
      if (d1 & D_VALID) issue(tmV, ring + so, bar, d1, dep_zero(last, zero));
      if (CFG_PFDELAY == 1) keep_late(prm.kbytes, d1);
      if (CFG_PFDELAY == 2) keep_late(prm.vbytes, d0);
    });
    advance();
    so = csp & 0x1800; bar = rbar + (csp >> 8);
    mbar_wait(bar, csp & 1);
    pv_smem(cur, laneV + so, pk, [&](uint32_t last) {
      if (d2 & D_VALID) issue(tmK, ring + so, bar, d2, dep_zero(last, zero));
      if (CFG_PFDELAY == 1) keep_late(prm.vbytes, d1);
      if (CFG_PFDELAY == 2) keep_late(prm.kbytes, d1);
    });
    LOG_STEP(2u);
    advance();
    d0 = d1; d1 = d2;
  };
  auto reg_step = [&](uint32_t* kf, uint32_t* vf, uint32_t b, bool staticNext, uint32_t dstatic) {
    const uint32_t d2 = staticNext ? dstatic : grab();
    csp = uni(csp);
    uint32_t so = csp & 0x1800, bar = rbar + (csp >> 8);
    mbar_wait(bar, csp & 1);
    {
      const uint32_t la = laneK + so;
      ldsm4(kf + 0, la); ldsm4(kf + 4, la ^ 32); ldsm4(kf + 8, la ^ 64); ldsm4(kf + 12, la ^ 96);
      if (d1 & D_VALID) issue(tmV, ring + so, bar, d1, dep_zero(kf[15], zero));
    }
    advance();
    const uint32_t pk = qk_reg(kf, qoff + b * 256, cur, lane);
    so = csp & 0x1800; bar = rbar + (csp >> 8);
    mbar_wait(bar, csp & 1);
    {
      const uint32_t la = laneV + so;
      ldsm4t(vf + 0, la); ldsm4t(vf + 4, la ^ 32); ldsm4t(vf + 8, la ^ 64); ldsm4t(vf + 12, la ^ 96);
      if (d2 & D_VALID) issue(tmK, ring + so, bar, d2, dep_zero(vf[15], zero));
    }
    pv_reg(vf, pk, cur, lane);
    LOG_STEP(2u);
    advance();
    d0 = d1; d1 = d2;
  };
  auto flush = [&](uint32_t b, uint32_t area, uint32_t bar) {
    ensure(b);
    float l = cur.l;
    l += __shfl_xor_sync(0xffffffffu, l, 4);
    l += __shfl_xor_sync(0xffffffffu, l, 8);
    l += __shfl_xor_sync(0xffffffffu, l, 16);
    const uint32_t e = area + ((lane & 3) * 16 + (lane >> 2)) * 4;
    stsf(e, cur.o0); stsf(e + 256, cur.o1); stsf(e + 32, cur.o2); stsf(e + 288, cur.o3);
    if (lane == 0) { stsf(area + 512, cur.m); stsf(area + 516, l); }
    __syncwarp();
    if (lane == 0) mbar_arrive(bar);
    cur.o0 = cur.o1 = cur.o2 = cur.o3 = cur.l = 0.f; cur.m = -INFINITY;
  };
  auto side_fill = [&](uint32_t i, uint32_t b, int dep) { side_fill_w(tmK, tmV, sb, side, wp, lane, i, b, dep); };
  const uint32_t pzu = uni(lds128(wp + 16).z), kblk = uni(lds32(wp) + 112);
  auto side_try = [&](const uint32_t j, const bool force) -> bool {
    const uint32_t bit = 1u << j;
    const uint32_t slot = (pzu & 255) + j * ((pzu >> 8) & 255);
    const uint32_t bar = sb + OFF_SBAR + slot * 8;
    const uint32_t b = (ss >> (SS_B + j)) & 1;
    bool cyc;
    if (ss & (bit << SS_F)) {
      const uint32_t par = (ss >> (SS_P + j)) & 1;
      if (force) mbar_wait(bar, par);
      else if (!__all_sync(0xffffffffu, mbar_test(bar, par))) return false;
      cyc = (ss & (bit << SS_K)) != 0;
      ss ^= (bit << SS_F) | (bit << SS_P);
    } else {
      if (!(st & (b ? ST_R1 : ST_R0))) {
        if (!force) return false;
        gate(b);
      }
      cyc = true;
      ss &= ~((bit << SS_H0) | (bit << SS_H1));
    }
    const uint4 kb = lds128(kblk);
    uint32_t u = 0;
    if (cyc) u = ticket_take(kb.w + b * 32);
    const uint32_t delta = side + slot * 4096 - ring;
    auto next_load = [&](uint32_t last) {
      if (cyc) {
        u = ticket_bcast(u);
        const int dep = dep_zero(last, zero);
        if (u < kb.x) {
          const int row = (int)(kb.y + b * TPB - u) * 16;
          tma_issue2(ring + delta, tmK, tmV, dep, row, bar);
          ss |= (bit << SS_F) | (bit << SS_K);
        } else if (!b) {
          side_fill(j, 1, dep);
          ss = (ss & ~(bit << SS_K)) | (bit << SS_F) | (bit << SS_B);
        } else {
          ss &= ~(bit << SS_K);
        }
      } else {
        ss |= bit << (b ? SS_H1 : SS_H0);
      }
    };
    if (b == ((st & ST_CURB) ? 1u : 0u)) {
      const uint32_t pk = qk_smem(cur, laneK + delta, qoff + b * 256, [&](uint32_t) {});
      pv_smem(cur, laneV + delta + 2048, pk, next_load);
    } else {
      const uint32_t pk = qk_smem(oth, laneK + delta, qoff + b * 256, [&](uint32_t) {});
      pv_smem(oth, laneV + delta + 2048, pk, next_load);
    }
    LOG_STEP(3u);
    return true;
  };

  ev = 0;
  uint32_t sfull;
  {
    const uint4 p = lds128(wp + 16);
    const uint32_t nside = p.z >> 24;
    sfull = (1u << nside) - 1;
    ss = sfull << SS_F;
    uint32_t sis = lds32(sb + OFF_HELD + w * 4);
    d0 = D_VALID | D_REG | D_B0 | p.w;
    d1 = D_VALID | D_REG | D_B0 | (p.w + 1);
#pragma unroll
    for (int i = 0; i < RP; i++) {
      if (sis < nside) side_fill(sis++, 0, 0);
      reg_step(&kv[i][0], &kv[i][16], 0, i + 2 < RP, D_VALID | D_REG | D_B0 | (lds128(wp + 16).w + i + 2));
    }
    while (sis < nside) side_fill(sis++, 0, 0);
  }
  ev = D_VALID | D_END;
  while (true) {
    uint32_t d2;
    if (d0 & ev) {
      if ((d0 & ev & ~(D_B0 | D_B1)) == 0) {
        ensure((d0 >> 16) & 1);
        ev ^= D_B0 | D_B1;
        d2 = grab();
      } else {
        const bool sonly = (d0 & ev & ~D_VALID) == 0 && (st & ST_SONLY);
        if (sonly) {
        } else if (!(st & ST_R0)) {
          if ((st & ST_FL0) && __all_sync(0xffffffffu, mbar_test(sb + BAR_R0, 0))) st |= ST_R0;
        } else if (!(st & ST_R1)) {
          if ((st & ST_FL1) && __all_sync(0xffffffffu, mbar_test(sb + BAR_R1, 0))) st |= ST_R1;
        }
        {
          const uint32_t sF = (ss >> SS_F) & 31, sH0 = (ss >> SS_H0) & 31, sH1 = (ss >> SS_H1) & 31;
          uint32_t need = 0;
          if (sonly) {}
          else if (!(st & ST_FL0)) { if (d0 & D_PAST0) need = sF; }
          else if (!(st & ST_FL1)) { if (d0 & D_PAST1) need = sfull & ~sH1; }
          else if (d0 & D_END) need = sF | sH0 | sH1;
          const bool force = need != 0;
          uint32_t cand = force ? need : (sF | ((st & ST_R0) ? sH0 : 0u) | ((st & ST_R1) ? sH1 : 0u));
          int budget = force ? 1 : CFG_SIDE_MAX;
          while (cand && budget) {
            if (CFG_SIDE_EVERY > 1 && !force && (d0 & D_VALID) && ((st >> SH_SKIP) & 7) < CFG_SIDE_EVERY - 1 &&
                (!CFG_RING_PRIO || __all_sync(0xffffffffu, mbar_test(rbar + (csp >> 8), csp & 1)))) {
              st += 1u << SH_SKIP;
              break;
            }
            st &= ~(7u << SH_SKIP);
            const uint32_t j = __ffs(cand) - 1;
            cand &= cand - 1;
            if (side_try(j, force)) budget--;
          }
          if (force) { ev |= D_VALID | D_END; st &= ~ST_SONLY; continue; }
        }
        if (sonly) {
          const uint32_t act = (ss >> SS_F) | ((st & ST_R0) ? (ss >> SS_H0) : 0u) | ((st & ST_R1) ? (ss >> SS_H1) : 0u);
          if (!(act & 31)) { ev &= ~D_VALID; st &= ~ST_SONLY; }
          d2 = grab();
          goto step;
        }
        {
        bool redo = true;
        if (!(st & ST_FL0) && (d0 & D_PAST0)) {
          flush(0, sb + OFF_PART + w * 528, sb + BAR_P0);
          st |= ST_FL0;
        } else if (d0 & D_REG) {
          gate(0);
#pragma unroll
          for (int i = 0; i < RP; i++) {
            if (i == 0) ensure(1);
            const uint32_t pk = qk_reg(&kv[i][0], qoff, oth, lane);
            pv_reg(&kv[i][16], pk, oth, lane);
            reg_step(&kv[i][0], &kv[i][16], 1, i + 2 < RP, reg_desc(i + 2));
          }
        } else if (!(st & ST_FL1) && (d0 & D_PAST1)) {
          flush(1, sb + OFF_PART + w * 528, sb + BAR_P0 + 8);
          st |= ST_FL1;
        } else if (!(st & ST_FL2) && (d0 & D_PAST2)) {
          gate(1);
          flush(0, sb + OFF_PART + w * 528, sb + BAR_P0 + 16);
          st |= ST_FL2;
        } else if (!(st & ST_REGC) && ((st & ST_R1) || (d0 & D_END))) {
          gate(1);
          ensure(1);
#pragma unroll
          for (int i = 0; i < RP; i++) {
            const uint32_t pk = qk_reg(&kv[i][0], qoff + 256, cur, lane);
            pv_reg(&kv[i][16], pk, cur, lane);
          }
          st |= ST_REGC;
        } else if (d0 & D_END) {
          break;
        } else {
          redo = false;
        }
        if (redo) { ev |= D_VALID | D_END; st &= ~ST_SONLY; continue; }
        if (d0 & D_N0) gate(0);
        if (d0 & D_N1) gate(1);
        ensure((d0 >> 16) & 1);
        bool forced = false;
        if (st & ST_INJ2) {
          st &= ~ST_INJ2;
          d2 = reg_desc(1);
          forced = true;
        } else if ((st & (ST_R0 | ST_INJ)) == ST_R0) {
          st |= ST_INJ | ST_INJ2;
          d2 = reg_desc(0);
          forced = true;
        }
        ev = D_REG | D_END | ((st & ST_CURB) ? D_B0 : D_B1) | ((st & ST_FL0) ? 0u : D_PAST0) |
             ((st & ST_FL1) ? 0u : D_PAST1) | ((st & ST_FL2) ? 0u : D_PAST2) | ((st & ST_R0) ? 0u : D_N0) |
             ((st & ST_R1) ? 0u : D_N1);
        const uint32_t act = (ss >> SS_F) | ((st & ST_R0) ? (ss >> SS_H0) : 0u) | ((st & ST_R1) ? (ss >> SS_H1) : 0u);
        st &= ~ST_SONLY;
        if ((st & ST_INJ2) || ((st & (ST_R1 | ST_REGC)) == ST_R1)) ev |= D_VALID;
        else if (act & 31) { ev |= D_VALID; st |= ST_SONLY; }
        if (((st & ST_FL0) && !(st & ST_R0)) || ((st & ST_FL1) && !(st & ST_R1))) ev |= 1;
        if (!forced) d2 = grab();
        }
      }
    } else {
      d2 = grab();
    }
  step:
    ring_step(d2);
    if (CFG_IDLE) __nanosleep(CFG_IDLE);
    if (CFG_IDLE_WAIT && (ev & 1)) __nanosleep(CFG_IDLE_WAIT);
  }
  flush(1, ring, sb + BAR_P0 + 24);
}

__device__ __forceinline__ void aux_layernorm(const uint32_t sb, const uint32_t dst, const int t, float x0, float x1,
                                              float x2, float x3) {
  float s = (x0 + x1) + (x2 + x3);
#pragma unroll
  for (int o = 16; o; o >>= 1) s += __shfl_xor_sync(0xffffffffu, s, o);
  const float mw = s * (1.f / 128);
  float v = ((x0 - mw) * (x0 - mw) + (x1 - mw) * (x1 - mw)) + ((x2 - mw) * (x2 - mw) + (x3 - mw) * (x3 - mw));
#pragma unroll
  for (int o = 16; o; o >>= 1) v += __shfl_xor_sync(0xffffffffu, v, o);
  if ((t & 31) == 0) { stsf(sb + OFF_RED + (t >> 5) * 4, mw); stsf(sb + OFF_RED + 16 + (t >> 5) * 4, v); }
  aux_sync();
  const uint4 rs = lds128(sb + OFF_RED), rv = lds128(sb + OFF_RED + 16);
  const float m0 = __uint_as_float(rs.x), m1 = __uint_as_float(rs.y), m2 = __uint_as_float(rs.z), m3 = __uint_as_float(rs.w);
  const float mean = ((m0 + m1) + (m2 + m3)) * 0.25f;
  const float var = (((__uint_as_float(rv.x) + __uint_as_float(rv.y)) + (__uint_as_float(rv.z) + __uint_as_float(rv.w))) +
                     128.f * (((m0 - mean) * (m0 - mean) + (m1 - mean) * (m1 - mean)) +
                              ((m2 - mean) * (m2 - mean) + (m3 - mean) * (m3 - mean)))) * (1.f / DM);
  const float m = bf16r(mean);
  const float den = bf16r(fsqrt_approx(bf16r(bf16r(var) + 1e-5f)));
  sts32(dst + t * 8, pack_bf16(__fdividef(bf16r(x0 - m), den), __fdividef(bf16r(x1 - m), den)));
  sts32(dst + t * 8 + 4, pack_bf16(__fdividef(bf16r(x2 - m), den), __fdividef(bf16r(x3 - m), den)));
  aux_sync();
}
__device__ __forceinline__ void cp16(uint32_t dst, const void* src) {
  asm volatile("cp.async.cg.shared.global.L2::cache_hint [%0], [%1], 16, %2;" ::"r"(dst), "l"(src), "l"(POL_FIRST) : "memory");
}
__device__ __forceinline__ void cp16_shared(uint32_t dst, const void* src) {
  asm volatile("cp.async.cg.shared.global [%0], [%1], 16;" ::"r"(dst), "l"(src) : "memory");
}
__device__ __forceinline__ void cp_wait_all() { asm volatile("cp.async.wait_all;" ::: "memory"); }
__device__ __forceinline__ void gemv_mma(float& c0, float& c1, float& c2, float& c3, uint32_t la, uint32_t astep,
                                         uint32_t xa, int nk) {
  float e0 = 0.f, e1 = 0.f, e2 = 0.f, e3 = 0.f;
#pragma unroll 1
  for (int k = 0; k < nk; k += 2) {
    uint32_t a[4], a2[4];
    ldsm4t(a, la);
    ldsm4t(a2, la + astep);
    const uint32_t b0 = lds32(xa), b1 = lds32(xa + 16), b2 = lds32(xa + 32), b3 = lds32(xa + 48);
    mma16816(c0, c1, c2, c3, a, b0, b1);
    mma16816(e0, e1, e2, e3, a2, b2, b3);
    la += 2 * astep;
    xa += 64;
  }
  c0 += e0; c1 += e1; c2 += e2; c3 += e3;
}
__device__ __forceinline__ uint32_t ll_raw(const uint32_t* p) {
  uint32_t w;
  asm volatile("ld.relaxed.gpu.global.u32 %0, [%1];" : "=r"(w) : "l"(p) : "memory");
  return w;
}
__device__ __forceinline__ uint2 ll_raw2(const uint32_t* p) {
  uint2 w;
  asm volatile("ld.relaxed.gpu.global.v2.u32 {%0,%1}, [%2];" : "=r"(w.x), "=r"(w.y) : "l"(p) : "memory");
  return w;
}
__device__ __forceinline__ bool ll_ok(uint32_t w, uint32_t tag) { return (w & 255) == tag; }
__device__ __forceinline__ float ll_val(uint32_t w) { return __uint_as_float(w & 0xffffff00u); }
__device__ __forceinline__ void ll_backoff(int& it) {
  if (++it > SPIN_LIMIT) __trap();
  __nanosleep(40);
}
__device__ __forceinline__ float ll_wait1(const uint32_t* p, uint32_t tag) {
  int it = 0;
  while (true) {
    const uint32_t w = ll_raw(p);
    if (ll_ok(w, tag)) return ll_val(w);
    ll_backoff(it);
  }
}
__device__ __forceinline__ void ll_wait4(const uint32_t* p, uint32_t tag, float& x0, float& x1, float& x2, float& x3) {
  int it = 0;
  while (true) {
    uint32_t a, b, c, d;
    asm volatile("ld.relaxed.gpu.global.v4.u32 {%0,%1,%2,%3}, [%4];" : "=r"(a), "=r"(b), "=r"(c), "=r"(d) : "l"(p) : "memory");
    if (ll_ok(a, tag) && ll_ok(b, tag) && ll_ok(c, tag) && ll_ok(d, tag)) {
      x0 = ll_val(a); x1 = ll_val(b); x2 = ll_val(c); x3 = ll_val(d);
      return;
    }
    ll_backoff(it);
  }
}
__device__ __forceinline__ void ll_wait2s(const uint32_t* p, int stride, uint32_t tag, float& x0, float& x1) {
  int it = 0;
  while (true) {
    const uint32_t a = ll_raw(p), b = ll_raw(p + stride);
    if (ll_ok(a, tag) && ll_ok(b, tag)) { x0 = ll_val(a); x1 = ll_val(b); return; }
    ll_backoff(it);
  }
}
__device__ __forceinline__ float warp_sum4(float v0, float v1, float v2, float v3, int lane) {
  const bool h16 = lane & 16, h8 = lane & 8;
  const float k0 = (h16 ? v2 : v0) + __shfl_xor_sync(0xffffffffu, h16 ? v0 : v2, 16);
  const float k1 = (h16 ? v3 : v1) + __shfl_xor_sync(0xffffffffu, h16 ? v1 : v3, 16);
  float k = (h8 ? k1 : k0) + __shfl_xor_sync(0xffffffffu, h8 ? k0 : k1, 8);
  k += __shfl_xor_sync(0xffffffffu, k, 4);
  k += __shfl_xor_sync(0xffffffffu, k, 2);
  k += __shfl_xor_sync(0xffffffffu, k, 1);
  return k;
}
__device__ __forceinline__ void hint_arrive(unsigned int* c, const int t) {
  aux_sync();
  if (t == 0) asm volatile("red.relaxed.gpu.global.add.u32 [%0], 1;" ::"l"(c) : "memory");
}
__device__ __forceinline__ void hint_wait(const unsigned int* c, uint32_t target, const int t) {
  if (t == 0) {
    int it = 0;
    while (true) {
      uint32_t v;
      asm volatile("ld.relaxed.gpu.global.u32 %0, [%1];" : "=r"(v) : "l"(c) : "memory");
      if ((int)(v - target) >= 0) break;
      if (++it > SPIN_LIMIT) __trap();
      __nanosleep(CFG_HINT_SLEEP);
    }
  }
  aux_sync();
}
__device__ __forceinline__ void aux_qproj(const uint32_t sb, const int t, int h, int r, uint32_t xn0, uint32_t xn1, int b0,
                                          int nb, uint32_t tag) {
  const int wq = t >> 5, lane = t & 31, mat = lane >> 3, g = lane >> 2;
  const int row = (wq >> 1) * 256 + (mat >> 1) * 8 + (lane & 7), ch = 2 * (wq & 1) + (mat & 1);
  float c0 = 0.f, c1 = 0.f, c2 = 0.f, c3 = 0.f;
  gemv_mma(c0, c1, c2, c3, sb + OFF_WQ + row * 64 + ((ch ^ ((row >> 1) & 3)) << 4), 1024,
           ((g & 1) ? xn1 : xn0) + ((wq >> 1) * 256 + 2 * (lane & 3)) * 2, 16);
  if ((lane & 3) == 0) {
    const uint32_t e = sb + SC_RED4 + ((wq >> 1) * 64 + (wq & 1) * 16 + g) * 4;
    stsf(e, c0); stsf(e + 32, c2); stsf(e + 128, c1); stsf(e + 160, c3);
  }
  aux_sync();
  if (t < 32 * nb)
    ll_st(&g_Q[b0 + (t >> 5)][h][r * 32 + (t & 31)], bf16r(ldsf(sb + SC_RED4 + t * 4) + ldsf(sb + SC_RED4 + (64 + t) * 4)), tag);
  aux_sync();
  if (t < nb) asm volatile("red.relaxed.gpu.global.add.u32 [%0], 1;" ::"l"(&g_cntQ[b0 + t][h]) : "memory");
}
__device__ __forceinline__ void qfrag_store(uint32_t qf, const int t, float q) {
  const int half = t >> 6, j = (t >> 4) & 3, k = t & 15;
  const uint32_t off = (j >> 1) * 128 + (half * 4 + ((k & 7) >> 1)) * 16 + ((j & 1) * 2 + (k >> 3)) * 4 + (k & 1) * 2;
  sts16(qf + off, (uint16_t)(__float_as_uint(q) >> 16));
}

__device__ __forceinline__ int aux_tid() {
  int t;
  asm volatile("mov.u32 %0, %%tid.x;" : "=r"(t));
  return t - 256;
}
#define AUX_STAGE() \
  t = aux_tid(); wq = t >> 5; lane = t & 31; mat = lane >> 3; g = lane >> 2; i8 = lane & 7

__device__ __forceinline__ void aux_chain(const Params& p, const uint32_t sb, const int c, const int b,
                                          const int layer, const uint32_t epoch, uint32_t area, uint32_t astride,
                                          uint32_t pbar) {
  const uint32_t tag = ll_tag(epoch, 1 + layer);
  const bool last = b && layer;
  const uint32_t use = 2 * (epoch - 1) + layer + 1;
  const int h = c >> 2, r = c & 3;
  int t, wq, lane, mat, g, i8;
  AUX_STAGE();
  const int nsrc = p.ht ? 5 : 4;
  if (t == 0) stamp2(b + 2 * layer, 0);
  mbar_wait(pbar, 0);
  if (t == 0) stamp(2 + 2 * (b + 2 * layer));
  {
    float M = -INFINITY;
#pragma unroll
    for (int k = 0; k < 8; k++) M = fmaxf(M, ldsf(area + k * astride + 512));
    M = ll_trunc(M);
    float O = 0.f, L = 0.f;
#pragma unroll 4
    for (int k = 0; k < 8; k++) {
      const float sc = ex2(ldsf(area + k * astride + 512) - M);
      O = fmaf(sc, ldsf(area + k * astride + t * 4), O);
      L = fmaf(sc, ldsf(area + k * astride + 516), L);
    }
    ll_st(&g_P[b][h][r][t], O, tag);
    if (t == 0) { ll_st(&g_P[b][h][r][128], M, tag); ll_st(&g_P[b][h][r][129], L, tag); }
  }
  hint_arrive(&g_cntP[b][h], t);
  hint_wait(&g_cntP[b][h], use * nsrc - (last ? 1 : 0), t);
  if (t == 0) stamp2(b + 2 * layer, 1);
  AUX_STAGE();
  {
    const uint32_t* P0 = &g_P[b][h][0][0];
    const int s4 = nsrc == 5 ? 528 : 0;
    uint32_t o0, o1, o2, o3, o4;
    uint2 q0, q1, q2, q3, q4;
    int it = 0;
    while (true) {
      o0 = ll_raw(P0 + t); o1 = ll_raw(P0 + 132 + t); o2 = ll_raw(P0 + 264 + t); o3 = ll_raw(P0 + 396 + t); o4 = ll_raw(P0 + s4 + t);
      q0 = ll_raw2(P0 + 128); q1 = ll_raw2(P0 + 260); q2 = ll_raw2(P0 + 392); q3 = ll_raw2(P0 + 524); q4 = ll_raw2(P0 + s4 + 128);
      const bool ok = ll_ok(o0, tag) && ll_ok(o1, tag) && ll_ok(o2, tag) && ll_ok(o3, tag) && ll_ok(o4, tag) &&
                      ll_ok(q0.x, tag) && ll_ok(q0.y, tag) && ll_ok(q1.x, tag) && ll_ok(q1.y, tag) && ll_ok(q2.x, tag) &&
                      ll_ok(q2.y, tag) && ll_ok(q3.x, tag) && ll_ok(q3.y, tag) && ll_ok(q4.x, tag) && ll_ok(q4.y, tag);
      if (ok) break;
      ll_backoff(it);
    }
    const float M = fmaxf(fmaxf(fmaxf(ll_val(q0.x), ll_val(q1.x)), fmaxf(ll_val(q2.x), ll_val(q3.x))), ll_val(q4.x));
    const float e0 = ex2(ll_val(q0.x) - M), e1 = ex2(ll_val(q1.x) - M), e2 = ex2(ll_val(q2.x) - M), e3 = ex2(ll_val(q3.x) - M);
    const float e4 = nsrc == 5 ? ex2(ll_val(q4.x) - M) : 0.f;
    const float L = (e0 * ll_val(q0.y) + e1 * ll_val(q1.y)) + (e2 * ll_val(q2.y) + e3 * ll_val(q3.y)) + e4 * ll_val(q4.y);
    const float o = __fdividef((e0 * ll_val(o0) + e1 * ll_val(o1)) + (e2 * ll_val(o2) + e3 * ll_val(o3)) + e4 * ll_val(o4), L);
    sts16(sb + SC_O + t * 2, (uint16_t)(pack_bf16(o, 0.f) & 0xffffu));
  }
  aux_sync();
  if (t == 0) stamp2(b + 2 * layer, 2);
  AUX_STAGE();
#pragma unroll 1
  for (int m = 0; m < 2; m++) {
    const int mt = 2 * wq + m;
    float c0 = 0.f, c1 = 0.f, c2 = 0.f, c3 = 0.f;
    gemv_mma(c0, c1, c2, c3, sb + OFF_WO + ((mat >> 1) * 8 + i8) * 256 + (((2 * mt + (mat & 1)) ^ i8) << 4), 4096,
             sb + SC_O + (lane & 3) * 4, 8);
    if ((lane & 3) < 2) ll_st(&g_Z[b][h][r * 128 + mt * 16 + g + 8 * (lane & 1)], (lane & 1) ? c2 : c0, tag);
  }
  hint_arrive(&g_cntZ[b][r], t);
  if (t == 0) stamp2(b + 2 * layer, 3);
  AUX_STAGE();
  hint_wait(&g_cntZ[b][c >> 5], use * NH - CFG_HINT_K, t);
  if (wq == 0) {
    float z0, z1, z2, z3;
    ll_wait4(&g_Z[b][lane][4 * c], tag, z0, z1, z2, z3);
    __syncwarp();
    const float xres = bf16r(ldsf(sb + OFF_XRES + (b * 4 + mat) * 4) + bf16r(warp_sum4(z0, z1, z2, z3, lane)));
    __syncwarp();
    if (i8 == 0) {
      stsf(sb + OFF_XRES + (b * 4 + mat) * 4, xres);
      ll_st(&g_X1[b][4 * c + mat], xres, tag);
    }
  }
  hint_arrive(&g_cntX1[b], t);
  if (t == 0) stamp2(b + 2 * layer, 4);
  AUX_STAGE();
  const int ng = ffn_groups(c);
  {
    float x0, x1, x2, x3;
    if (!last) hint_wait(&g_cntX1[b], use * NMAIN - 4 * CFG_HINT_K, t);
    ll_wait4(&g_X1[b][4 * t], tag, x0, x1, x2, x3);
    if (t == 0) stamp2(b + 2 * layer, 5);
    aux_layernorm(sb, sb + OFF_XN, t, x0, x1, x2, x3);
  }
  AUX_STAGE();
#pragma unroll 1
  for (int gi = 0; gi < ng; gi++) {
    float c0 = 0.f, c1 = 0.f, c2 = 0.f, c3 = 0.f;
    gemv_mma(c0, c1, c2, c3, sb + OFF_WF + gi * WF_BYTES + (mat & 1) * 8192 + (wq * 128 + (mat >> 1) * 8 + i8) * 16, 256,
             sb + OFF_XN + (wq * 128 + 2 * (lane & 3)) * 2, 8);
    if ((lane & 3) == 0) {
      const uint32_t e = sb + SC_RED4 + ((gi * 4 + wq) * 16 + g) * 4;
      stsf(e, c0); stsf(e + 32, c2);
    }
  }
  aux_sync();
  if (t < 8 * ng) {
    const uint32_t e = sb + SC_RED4 + ((t >> 3) * 64 + (t & 7)) * 4;
    const float gt = ldsf(e) + ldsf(e + 64) + ldsf(e + 128) + ldsf(e + 192);
    const float up = ldsf(e + 32) + ldsf(e + 96) + ldsf(e + 160) + ldsf(e + 224);
    ll_st(&g_H[b][((t >> 3) ? ffn_second(c) : c) * 8 + (t & 7)], bf16r(bf16r(gt) * bf16r(up)), tag);
  }
  hint_arrive(&g_cntD[b], t);
  if (t == 0) stamp2(b + 2 * layer, 7);
  AUX_STAGE();
  if (!last) hint_wait(&g_cntD[b], use * NMAIN - 4 * CFG_HINT_K, t);
  {
    const uint32_t* hp = &g_H[b][t];
    const bool has10 = t < FF - 1280;
    uint32_t hw[11];
    int it = 0;
    while (true) {
      bool ok = true;
#pragma unroll
      for (int i = 0; i < 10; i++) hw[i] = ll_raw(hp + 128 * i);
      hw[10] = has10 ? ll_raw(hp + 1280) : tag;
#pragma unroll
      for (int i = 0; i < 11; i++) ok = ok && ll_ok(hw[i], tag);
      if (ok) break;
      ll_backoff(it);
    }
    float d0 = 0.f, d1 = 0.f, d2 = 0.f, d3 = 0.f;
#pragma unroll
    for (int i = 0; i < 11; i++) {
      const uint2 v = lds64(sb + OFF_WD + (has10 || i < 10 ? t + 128 * i : t) * 8);
      const float hh = ll_val(hw[i]);
      d0 = fmaf(hh, bflo(v.x), d0); d1 = fmaf(hh, bfhi(v.x), d1);
      d2 = fmaf(hh, bflo(v.y), d2); d3 = fmaf(hh, bfhi(v.y), d3);
    }
    __syncwarp();
    const float d = warp_sum4(d0, d1, d2, d3, lane);
    if (i8 == 0) stsf(sb + SC_RED4 + (wq * 4 + mat) * 4, d);
    aux_sync();
    if (wq == 0) {
      const uint32_t e = sb + SC_RED4 + mat * 4;
      const float xres = bf16r(ldsf(sb + OFF_XRES + (b * 4 + mat) * 4) +
                               bf16r((ldsf(e) + ldsf(e + 16)) + (ldsf(e + 32) + ldsf(e + 48))));
      __syncwarp();
      if (i8 == 0) {
        stsf(sb + OFF_XRES + (b * 4 + mat) * 4, xres);
        if (layer == 0) ll_st(&g_X2[b][4 * c + mat], xres, tag);
        else p.out[b * DM + 4 * c + mat] = __float2bfloat16_rn(xres);
      }
    }
    if (layer == 0) hint_arrive(&g_cntX2[b], t);
  }
  if (t == 0) stamp2(b + 2 * layer, 8);
  AUX_STAGE();
  if (layer == 0) {
    {
      float x0, x1, x2, x3;
      hint_wait(&g_cntX2[b], epoch * NMAIN - 4 * CFG_HINT_K, t);
      ll_wait4(&g_X2[b][4 * t], tag, x0, x1, x2, x3);
      if (t == 0) stamp2(b + 2 * layer, 9);
      aux_layernorm(sb, sb + OFF_XN, t, x0, x1, x2, x3);
    }
    AUX_STAGE();
    aux_qproj(sb, t, h, r, sb + OFF_XN, sb + OFF_XN, b, 1, tag);
    AUX_STAGE();
    if (t == 0) stamp2(b + 2 * layer, 10);
    int bq;
    asm volatile("mov.u32 %0, %1;" : "=r"(bq) : "r"(b));
    hint_wait(&g_cntQ[bq][h], epoch * 8 - (CFG_HINT_K ? 1 : 0), t);
    qfrag_store(sb + OFF_QF + b * 256, t, ll_wait1(&g_Q[b][h][t], tag));
    aux_sync();
    if (t == 0) mbar_arrive(sb + (b ? BAR_R1 : BAR_R0));
  }
}

__device__ __forceinline__ void aux_fill_wq(const Params& p, const uint32_t sb, const int t, const int c) {
  const int h = c >> 2, r = c & 3;
#pragma unroll 4
  for (int i = 0; i < 16; i++) {
    const int row = i * 32 + (t >> 2), ch = t & 3;
    cp16(sb + OFF_WQ + row * 64 + ((ch ^ ((row >> 1) & 3)) << 4), p.wq + (size_t)row * (NH * 128) + h * 128 + r * 32 + ch * 8);
  }
}
__device__ __forceinline__ void aux_fill_rest(const Params& p, const uint32_t sb, const int t, const int c) {
  const int h = c >> 2, r = c & 3;
#pragma unroll 1
  for (int i = 0; i < 16; i++) {
    const int row = i * 8 + (t >> 4), ch = t & 15;
    cp16(sb + OFF_WO + row * 256 + ((ch ^ (row & 7)) << 4), p.wo + (size_t)(h * 128 + row) * DM + r * 128 + ch * 8);
    if ((i & 3) == 3) cp_wait_all();
  }
  const int ng = ffn_groups(c);
#pragma unroll 1
  for (int gi = 0; gi < ng; gi++) {
    const int G = gi ? ffn_second(c) : c;
    const uint32_t base = sb + OFF_WF + gi * WF_BYTES;
#pragma unroll 1
    for (int i = 0; i < 4; i++) {
      const int q = i * 128 + t;
      cp16_shared(base + q * 16, p.wg + (size_t)q * FF + G * 8);
      cp16_shared(base + 8192 + q * 16, p.wu + (size_t)q * FF + G * 8);
      if (i & 1) cp_wait_all();
    }
  }
#pragma unroll 1
  for (int f = t; f < FF; f += 128) {
    asm volatile("cp.async.ca.shared.global [%0], [%1], 8;" ::"r"(sb + OFF_WD + f * 8), "l"(p.wd + (size_t)f * DM + 4 * c)
                 : "memory");
    if ((f >> 7) % 4 == 3) cp_wait_all();
  }
  cp_wait_all();
  aux_sync();
}

__device__ __forceinline__ void aux_init_main(const Params& p, const uint32_t sb, const int t, const int c, const uint32_t tag) {
  const uint2 xa = *reinterpret_cast<const uint2*>(p.x + 4 * t);
  const uint2 xb = *reinterpret_cast<const uint2*>(p.x + DM + 4 * t);
  if (t == 0) stamp2(0, 14);
  aux_layernorm(sb, sb + OFF_XN, t, bflo(xa.x), bfhi(xa.x), bflo(xa.y), bfhi(xa.y));
  aux_layernorm(sb, sb + SC_XN1, t, bflo(xb.x), bfhi(xb.x), bflo(xb.y), bfhi(xb.y));
  cp_wait_all();
  aux_sync();
  if (t == 0) stamp2(1, 14);
  aux_qproj(sb, t, c >> 2, c & 3, sb + OFF_XN, sb + SC_XN1, 0, 2, tag);
  if (t == 0) stamp2(2, 14);
}

__device__ __forceinline__ void aux_main(const Params& p, const uint32_t sb, const int t, const int c, const uint32_t epoch) {
  const int h = c >> 2;
  const uint32_t tag0 = ll_tag(epoch, 0);
  {
    float q0, q1;
    ll_wait2s(&g_Q[0][h][t], NH * 128, tag0, q0, q1);
    qfrag_store(sb + OFF_QF, t, q0);
    qfrag_store(sb + OFF_QF + 256, t, q1);
  }
  aux_sync();
  if (t == 0) mbar_arrive(sb + BAR_Q1);
  if (t == 0) stamp(1);
  aux_fill_rest(p, sb, t, c);
  if (t < 8) stsf(sb + OFF_XRES + t * 4, __bfloat162float(p.x[(t >> 2) * DM + 4 * c + (t & 3)]));
  aux_sync();
#pragma unroll 1
  for (int k = 0; k < 4; k++) {
    const int b = k & 1, layer = k >> 1;
    aux_chain(p, sb, c, b, layer, epoch, k == 3 ? sb + OFF_RING : sb + OFF_PART, k == 3 ? RING_W : 528,
              sb + BAR_P0 + 8 * k);
    if (t == 0) stamp(3 + 2 * k);
  }
}

__device__ __forceinline__ void aux_helper(const uint32_t sb, const int t, const int j, const uint32_t epoch) {
  const uint32_t tag0 = ll_tag(epoch, 0), tag1 = ll_tag(epoch, 1), tag2 = ll_tag(epoch, 2);
  const uint32_t qf = sb + OFF_QF_HELP;
#pragma unroll 1
  for (int w = 0; w < 8; w++) {
    hint_wait(&g_cntQ[1][8 * j + w], epoch * 8 - 4, t);
    for (int b = 0; b < 2; b++) qfrag_store(qf + w * 512 + b * 256, t, ll_wait1(&g_Q[b][8 * j + w][t], tag0));
  }
  aux_sync();
  if (t == 0) mbar_arrive(sb + BAR_Q1);
#pragma unroll 1
  for (int k = 0; k < 4; k++) {
    const int b = k & 1, layer = k >> 1;
    const uint32_t tag = layer ? tag2 : tag1;
    const uint32_t area = k == 3 ? sb + OFF_RING : sb + OFF_PART, astride = k == 3 ? RING_W : 528;
    mbar_wait(sb + BAR_P0 + 8 * k, 0);
    for (int w = 0; w < 8; w++) {
      const float m = ldsf(area + w * astride + 512), mt = ll_trunc(m), sc = ex2(m - mt);
      ll_st(&g_P[b][8 * j + w][4][t], sc * ldsf(area + w * astride + t * 4), tag);
      if (t < 2) ll_st(&g_P[b][8 * j + w][4][128 + t], t ? sc * ldsf(area + w * astride + 516) : mt, tag);
    }
    aux_sync();
    if (t < 8) asm volatile("red.relaxed.gpu.global.add.u32 [%0], 1;" ::"l"(&g_cntP[b][8 * j + t]) : "memory");
    if (layer == 0) {
#pragma unroll 1
      for (int w = 0; w < 8; w++) {
        hint_wait(&g_cntQ[b][8 * j + w], epoch * 8, t);
        qfrag_store(qf + w * 512 + b * 256, t, ll_wait1(&g_Q[b][8 * j + w][t], tag1));
      }
      aux_sync();
      if (t == 0) mbar_arrive(sb + (b ? BAR_R1 : BAR_R0));
    }
  }
}

__global__ void __launch_bounds__(384, 1)
fused_decode_kernel(const __grid_constant__ CUtensorMap tmK, const __grid_constant__ CUtensorMap tmV,
                    const __grid_constant__ Params p) {
  extern __shared__ __align__(1024) uint8_t smem[];
  if (threadIdx.x == 0) stamp(14);
  const uint32_t sb = (uint32_t)__cvta_generic_to_shared(smem);
  const int tid = threadIdx.x;
  const int w = __shfl_sync(0xffffffffu, tid >> 5, 0);
  const int lane = tid & 31;
  const int c = blockIdx.x;
  const bool helper = c >= NMAIN;

  const uint32_t side = sb + (helper ? OFF_W + 4096 : OFF_WF + ffn_groups(c) * WF_BYTES);
  if (w < 8) {
    if (lane == 0) {
      const int h = helper ? (c - NMAIN) * 8 + w : c >> 2, r = helper ? 4 : c & 3;
      const uint32_t q = helper ? p.q >> 3 : p.q;
      uint32_t own[5], total = 0, start = 0;
#pragma unroll
      for (int i = 0; i < 5; i++) {
        const uint32_t slots = (SMEM_BYTES - (OFF_WF + ffn_groups(4 * h + (i & 3)) * WF_BYTES)) >> 12;
        own[i] = i < 4 ? 8 * RP + slots + p.q : (p.ht ? RP + S_HELP_W + (p.q >> 3) : 0);
        if (i < r) start += own[i];
        total += own[i];
      }
      const uint32_t np = TPH - total;
      const uint32_t n1 = TPH - p.ht;
      uint32_t p1o = 0, p1n = 0;
#pragma unroll
      for (int i = 0; i < 5; i++) {
        const uint32_t cnt = i < 4 ? ((n1 + i) >> 2) - own[i] : p.ht - own[4];
        if (i < r) p1o += cnt;
        if (i == r) p1n = cnt;
      }
      const uint32_t h2 = p.ht ? p.h2 + (h < 12 ? 6 : 0) : 0, n2 = np - h2;
      const uint32_t p2n = helper ? h2 : (n2 + r) >> 2;
      uint32_t p2o = 0;
#pragma unroll
      for (int i = 0; i < 4; i++) if (i < r) p2o += (n2 + i) >> 2;
      const uint32_t hb = h * TPH, base = hb + start, zone = hb + total;
      uint32_t ctr, qf, st0, pk, rt, keep;
      if (!helper) {
        const uint32_t ns = (sb + SMEM_BYTES - side) >> 12;
        rt = base + w * RP;
        st0 = base + 8 * RP + w;
        pk = w | (8u << 8) | (8u << 16) | (((ns - w + 7) >> 3) << 24);
        keep = base + 8 * RP + ns;
        ctr = sb + OFF_CTR;
        qf = sb + OFF_QF;
      } else {
        rt = base;
        st0 = base + RP;
        pk = (w * S_HELP_W) | (1u << 8) | (1u << 16) | ((uint32_t)S_HELP_W << 24);
        keep = base + RP + S_HELP_W;
        ctr = sb + OFF_CTR + w * 4;
        qf = sb + OFF_QF_HELP + w * 512;
      }
      const uint32_t wp = sb + OFF_WP + w * 32;
      const uint32_t seg = helper ? side + 8 * S_HELP_W * 4096 + w * 128 : sb + OFF_SEG;
      sts32(wp, seg); sts32(wp + 4, ctr);
      sts32(wp + 16, qf); sts32(wp + 20, st0); sts32(wp + 24, pk); sts32(wp + 28, rt);
      if (helper || w == 0) {
        auto blk = [&](int i, uint32_t lim, uint32_t base_d, uint32_t pf, uint32_t cnt) {
          sts32(seg + i * 16, lim); sts32(seg + i * 16 + 4, base_d); sts32(seg + i * 16 + 8, pf); sts32(seg + i * 16 + 12, cnt);
        };
        const uint32_t t0 = p1n, t1 = t0 + q, t2 = t1 + p1n, t3 = t2 + q, t4 = t3 + p2n, t5 = t4 + p2n;
        blk(0, t0, (D_VALID | D_B0) + zone + p1o, 0xffffffffu, 0);
        blk(1, t1, (D_VALID | D_B0) + keep - t0, 0, 0);
        blk(2, t2, (D_VALID | D_B1 | D_PAST0) + zone + p1o + TPB - t1, 0xffffffffu, 0);
        blk(3, t3, (D_VALID | D_B1 | D_PAST0) + keep + TPB - t2, 0, 0);
        blk(4, t4, (D_VALID | D_B0 | D_N0 | D_PAST0 | D_PAST1) + zone + p2o - t3, 0xffffffffu, 0);
        blk(5, t5, (D_VALID | D_B1 | D_N1 | D_PASTS) + zone + p2o + (helper ? 0 : 0) + TPB - t4, 0xffffffffu, 0);
        blk(6, 0, 0, 0xffffffffu, 0);
        blk(7, q, keep + q - 1, 0, ctr + 32);
      }
      for (int s = 0; s < 4; s++) mbar_init(sb + OFF_RBAR + (w * 4 + s) * 8, 1);
      for (int s = w; s < 40; s += 8) mbar_init(sb + OFF_SBAR + s * 8, 1);
    }
  } else {
    if (!helper) aux_fill_wq(p, sb, tid - 256, c);
    if (w == 8) {
      if (lane < 24) sts32(sb + OFF_CTR + lane * 4, 0);
      if (lane == 0) {
        mbar_init(sb + BAR_Q1, 1); mbar_init(sb + BAR_R0, 1); mbar_init(sb + BAR_R1, 1);
        for (int k = 0; k < 4; k++) mbar_init(sb + BAR_P0 + 8 * k, 8);
      }
    }
  }
  asm volatile("fence.mbarrier_init.release.cluster;" ::: "memory");
  asm volatile("fence.proxy.async.shared::cta;" ::: "memory");
  __syncthreads();
  if (tid == 0) stamp(0);

  if (w < 8) {
    stream_prologue(&tmK, &tmV, sb, side, w, lane);
    asm volatile("setmaxnreg.inc.sync.aligned.u32 %0;" ::"n"(CFG_REG_S));
    int lane2;
    asm volatile("mov.u32 %0, %%laneid;" : "=r"(lane2));
    stream_warp(&tmK, &tmV, sb, side, w, lane2, p);
  } else {
    uint32_t epoch;
    asm volatile("ld.relaxed.gpu.global.u32 %0, [%1];" : "=r"(epoch) : "l"(&g_epoch) : "memory");
    epoch += 1;
    if (!helper) aux_init_main(p, sb, tid - 256, c, ll_tag(epoch, 0));
    asm volatile("setmaxnreg.dec.sync.aligned.u32 %0;" ::"n"(CFG_REG_A));
    int t;
    asm volatile("mov.u32 %0, %%tid.x;" : "=r"(t));
    t -= 256;
    if (!helper) aux_main(p, sb, t, c, epoch);
    else aux_helper(sb, t, c - NMAIN, epoch);
    if (c == 0 && t == 0) asm volatile("st.relaxed.gpu.global.u32 [%0], %1;" ::"l"(&g_epoch), "r"(epoch) : "memory");
    if (t == 0) stamp(13);
  }
}

typedef CUresult (*EncodeTiledFn)(CUtensorMap*, CUtensorMapDataType, cuuint32_t, void*, const cuuint64_t*,
                                  const cuuint64_t*, const cuuint32_t*, const cuuint32_t*, CUtensorMapInterleave,
                                  CUtensorMapSwizzle, CUtensorMapL2promotion, CUtensorMapFloatOOBfill);

}

extern "C" void kernel_launch(void* const* d_in, const int* in_sizes, int n_in, void* d_out, int out_size) {
  (void)in_sizes; (void)n_in; (void)out_size;
  static EncodeTiledFn encode = nullptr;
  static int sms = 0;
  if (!encode) {
    void* fn = nullptr;
    cudaDriverEntryPointQueryResult qr;
    cudaGetDriverEntryPoint("cuTensorMapEncodeTiled", &fn, cudaEnableDefault, &qr);
    encode = (EncodeTiledFn)fn;
    int dev = 0;
    cudaGetDevice(&dev);
    cudaDeviceGetAttribute(&sms, cudaDevAttrMultiProcessorCount, dev);
    cudaFuncSetAttribute(fused_decode_kernel, cudaFuncAttributeMaxDynamicSharedMemorySize, SMEM_BYTES);
  }
  CUtensorMap tmK, tmV;
  const cuuint64_t gdim[2] = {64, (cuuint64_t)2 * NH * SK * 2};
  const cuuint64_t gstr[1] = {128};
  const cuuint32_t box[2] = {64, 16};
  const cuuint32_t estr[2] = {1, 1};
  encode(&tmK, CU_TENSOR_MAP_DATA_TYPE_BFLOAT16, 2, d_in[1], gdim, gstr, box, estr, CU_TENSOR_MAP_INTERLEAVE_NONE,
         CU_TENSOR_MAP_SWIZZLE_128B, CU_TENSOR_MAP_L2_PROMOTION_NONE, CU_TENSOR_MAP_FLOAT_OOB_FILL_NONE);
  encode(&tmV, CU_TENSOR_MAP_DATA_TYPE_BFLOAT16, 2, d_in[2], gdim, gstr, box, estr, CU_TENSOR_MAP_INTERLEAVE_NONE,
         CU_TENSOR_MAP_SWIZZLE_128B, CU_TENSOR_MAP_L2_PROMOTION_NONE, CU_TENSOR_MAP_FLOAT_OOB_FILL_NONE);
  Params p;
  p.x = (const __nv_bfloat16*)d_in[0];
  p.wq = (const __nv_bfloat16*)d_in[3];
  p.wo = (const __nv_bfloat16*)d_in[4];
  p.wg = (const __nv_bfloat16*)d_in[6];
  p.wu = (const __nv_bfloat16*)d_in[7];
  p.wd = (const __nv_bfloat16*)d_in[8];
  p.out = (__nv_bfloat16*)d_out;
  const bool helpers = sms >= NMAIN + NHELP;
  p.ht = helpers ? CFG_HT : 0;
  p.h2 = CFG_H2;
  p.q = CFG_Q;
  p.zero = 0;
  p.kbytes = (const uint8_t*)d_in[1];
  p.vbytes = (const uint8_t*)d_in[2];
  fused_decode_kernel<<<helpers ? NMAIN + NHELP : NMAIN, 384, SMEM_BYTES, cudaStreamPerThread>>>(tmK, tmV, p);
}
```

```cpp
#include <cuda_runtime.h>
#include <cuda_bf16.h>
#include <cuda.h>
#include <stdint.h>

namespace {

constexpr int DM = 512;
constexpr int NH = 32;
constexpr int SK = 16384;
constexpr int FF = 1376;
constexpr int TPH = SK / 8;
constexpr int TPB = NH * TPH;

constexpr int RP = 6;
constexpr int REG_STREAM = 232;
constexpr int REG_AUX = 40;
constexpr int KEEP_L2 = 144;
constexpr int HELP_P1 = 56;
constexpr int HELP_P2 = 30;
constexpr int NMAIN = 128;
constexpr int NHELP = 4;
constexpr int S_HELP_W = 5;
constexpr int NGRP = FF / 8;
static_assert(NGRP - NMAIN == NH + 12, "second ffn groups: quarter 0 of every head, quarter 1 of the first 12 heads");
__host__ __device__ constexpr int ffn_groups(int c) { return ((c & 3) == 0 || ((c & 3) == 1 && (c >> 2) < 12)) ? 2 : 1; }
__host__ __device__ constexpr int ffn_second(int c) { return NMAIN + (c >> 2) + ((c & 3) ? NH : 0); }

constexpr uint32_t SMEM_BYTES = 232448;
constexpr uint32_t OFF_RING = 0;
constexpr uint32_t RING_W = 3 * 2048;
constexpr uint32_t OFF_MISC = 8 * RING_W;
constexpr uint32_t OFF_RBAR = OFF_MISC;
constexpr uint32_t OFF_SBAR = OFF_RBAR + 32 * 8;
constexpr uint32_t OFF_CBAR = OFF_SBAR + 40 * 8;
constexpr uint32_t BAR_Q1 = OFF_CBAR + 0, BAR_R0 = OFF_CBAR + 8, BAR_R1 = OFF_CBAR + 16;
constexpr uint32_t BAR_P0 = OFF_CBAR + 24;
constexpr uint32_t OFF_CTR = OFF_CBAR + 56;
constexpr uint32_t OFF_HELD = OFF_CTR + 96;
constexpr uint32_t OFF_WP = OFF_MISC + 768;
constexpr uint32_t OFF_QF = OFF_WP + 256;
constexpr uint32_t OFF_PART = OFF_QF + 512;
constexpr uint32_t OFF_XN = OFF_PART + 8 * 132 * 4;
constexpr uint32_t OFF_RED = OFF_XN + 1024;
constexpr uint32_t OFF_XRES = OFF_RED + 32;
constexpr uint32_t OFF_SEG = OFF_RED + 64;
constexpr uint32_t OFF_W = OFF_MISC + 7168;
constexpr uint32_t OFF_WQ = OFF_W;
constexpr uint32_t OFF_WO = OFF_WQ + 32768;
constexpr uint32_t OFF_WD = OFF_WO + 32768;
constexpr uint32_t OFF_WF = OFF_WD + 11264;
constexpr uint32_t WF_BYTES = 16384;
constexpr uint32_t OFF_QF_HELP = OFF_W;
static_assert(OFF_HELD + 32 <= OFF_WP, "smem map");
static_assert(OFF_SEG + 128 <= OFF_W && OFF_W % 1024 == 0 && OFF_WF % 1024 == 0, "smem map");
constexpr uint32_t SC_RED4 = OFF_PART;
constexpr uint32_t SC_XN1 = OFF_PART + 1024;
constexpr uint32_t SC_O = OFF_PART + 2048;

__device__ __align__(16) uint32_t g_P[2][NH][5][132];
__device__ __align__(16) uint32_t g_Z[2][NH][DM];
__device__ __align__(16) uint32_t g_X1[2][DM];
__device__ __align__(16) uint32_t g_H[2][FF];
__device__ __align__(16) uint32_t g_X2[2][DM];
__device__ __align__(16) uint32_t g_Q[2][NH][128];
__device__ unsigned int g_epoch;
__device__ unsigned int g_cntP[2][NH], g_cntQ[2][NH], g_cntZ[2][4], g_cntX1[2], g_cntD[2], g_cntX2[2];

struct Params {
  const __nv_bfloat16* x;
  const __nv_bfloat16* wq;
  const __nv_bfloat16* wo;
  const __nv_bfloat16* wg;
  const __nv_bfloat16* wu;
  const __nv_bfloat16* wd;
  __nv_bfloat16* out;
  int ht;
  int h2;
  int q;
  uint32_t zero;
  const uint8_t* kbytes;
  const uint8_t* vbytes;
};

constexpr uint32_t D_TILE = 0x1FFFFu;
constexpr uint32_t D_B0 = 1u << 17, D_B1 = 1u << 18;
constexpr uint32_t D_N0 = 1u << 19, D_N1 = 1u << 20;
constexpr uint32_t D_PF = 1u << 21;
constexpr uint32_t D_REG = 1u << 22;
constexpr uint32_t D_PAST0 = 1u << 23, D_PAST1 = 1u << 24, D_PAST2 = 1u << 25;
constexpr uint32_t D_VALID = 1u << 26, D_END = 1u << 27;
constexpr uint32_t D_PASTS = D_PAST0 | D_PAST1 | D_PAST2;
constexpr uint32_t ST_R0 = 1u << 0, ST_R1 = 1u << 1, ST_INJ = 1u << 2, ST_INJ2 = 1u << 3, ST_FL0 = 1u << 7,
                   ST_FL1 = 1u << 8, ST_FL2 = 1u << 9, ST_REGC = 1u << 10, ST_CURB = 1u << 11,
                   ST_SONLY = 1u << 12;
constexpr int SS_F = 0, SS_H0 = 5, SS_H1 = 10, SS_B = 15, SS_K = 20, SS_P = 25;

constexpr uint64_t POL_FIRST = 0x12F0000000000000ull;
constexpr uint64_t POL_NORMAL = 0x16F0000000000000ull;
constexpr float SCALE_LOG2 = 0.08838834764831845f * 1.4426950408889634f;
constexpr int SPIN_LIMIT = 1 << 22;

__device__ __forceinline__ void mbar_init(uint32_t bar, uint32_t cnt) {
  asm volatile("mbarrier.init.shared::cta.b64 [%0], %1;" ::"r"(bar), "r"(cnt) : "memory");
}
__device__ __forceinline__ void mbar_expect_tx(uint32_t bar, uint32_t bytes) {
  asm volatile("mbarrier.arrive.expect_tx.shared::cta.b64 _, [%0], %1;" ::"r"(bar), "r"(bytes) : "memory");
}
__device__ __forceinline__ void mbar_arrive(uint32_t bar) {
  asm volatile("mbarrier.arrive.shared::cta.b64 _, [%0];" ::"r"(bar) : "memory");
}
__device__ __forceinline__ bool mbar_test(uint32_t bar, uint32_t parity) {
  uint32_t ok;
  asm volatile("{\n.reg .pred p;\nmbarrier.test_wait.parity.shared::cta.b64 p, [%1], %2;\nselp.u32 %0, 1, 0, p;\n}"
               : "=r"(ok) : "r"(bar), "r"(parity) : "memory");
  return ok != 0;
}
__device__ __forceinline__ bool mbar_try(uint32_t bar, uint32_t parity) {
  uint32_t ok;
  asm volatile("{\n.reg .pred p;\nmbarrier.try_wait.parity.shared::cta.b64 p, [%1], %2;\nselp.u32 %0, 1, 0, p;\n}"
               : "=r"(ok) : "r"(bar), "r"(parity) : "memory");
  return ok != 0;
}
__device__ __forceinline__ void mbar_wait(uint32_t bar, uint32_t parity) {
  int it = 0;
  while (!__all_sync(0xffffffffu, mbar_try(bar, parity)))
    if (++it > SPIN_LIMIT) __trap();
}
__device__ __forceinline__ void tma_load(uint32_t dst, const CUtensorMap* tm, int c0, int row, uint32_t bar) {
  asm volatile(
      "cp.async.bulk.tensor.2d.shared::cluster.global.tile.mbarrier::complete_tx::bytes.L2::cache_hint"
      " [%0], [%1, {%2, %3}], [%4], %5;" ::"r"(dst), "l"(tm), "r"(c0), "r"(row), "r"(bar), "l"(POL_FIRST)
      : "memory");
}
__device__ __forceinline__ void ldsm4(uint32_t* r, uint32_t addr) {
  asm volatile("ldmatrix.sync.aligned.m8n8.x4.shared.b16 {%0,%1,%2,%3}, [%4];"
               : "=r"(r[0]), "=r"(r[1]), "=r"(r[2]), "=r"(r[3]) : "r"(addr) : "memory");
}
__device__ __forceinline__ void ldsm4t(uint32_t* r, uint32_t addr) {
  asm volatile("ldmatrix.sync.aligned.m8n8.x4.trans.shared.b16 {%0,%1,%2,%3}, [%4];"
               : "=r"(r[0]), "=r"(r[1]), "=r"(r[2]), "=r"(r[3]) : "r"(addr) : "memory");
}
__device__ __forceinline__ void mma16816(float& d0, float& d1, float& d2, float& d3, const uint32_t* a, uint32_t b0,
                                         uint32_t b1) {
  asm("mma.sync.aligned.m16n8k16.row.col.f32.bf16.bf16.f32 {%0,%1,%2,%3}, {%4,%5,%6,%7}, {%8,%9}, {%0,%1,%2,%3};"
      : "+f"(d0), "+f"(d1), "+f"(d2), "+f"(d3)
      : "r"(a[0]), "r"(a[1]), "r"(a[2]), "r"(a[3]), "r"(b0), "r"(b1));
}
__device__ __forceinline__ void mma16816v(float& d0, float& d1, float& d2, float& d3, const uint32_t* a, uint32_t b0,
                                          uint32_t b1) {
  asm volatile("mma.sync.aligned.m16n8k16.row.col.f32.bf16.bf16.f32 {%0,%1,%2,%3}, {%4,%5,%6,%7}, {%8,%9}, {%0,%1,%2,%3};"
               : "+f"(d0), "+f"(d1), "+f"(d2), "+f"(d3)
               : "r"(a[0]), "r"(a[1]), "r"(a[2]), "r"(a[3]), "r"(b0), "r"(b1));
}
__device__ __forceinline__ uint32_t lds32(uint32_t a) {
  uint32_t v;
  asm volatile("ld.shared.u32 %0, [%1];" : "=r"(v) : "r"(a) : "memory");
  return v;
}
__device__ __forceinline__ uint2 lds64(uint32_t a) {
  uint2 v;
  asm volatile("ld.shared.v2.u32 {%0,%1}, [%2];" : "=r"(v.x), "=r"(v.y) : "r"(a) : "memory");
  return v;
}
__device__ __forceinline__ uint4 lds128(uint32_t a) {
  uint4 v;
  asm volatile("ld.shared.v4.u32 {%0,%1,%2,%3}, [%4];" : "=r"(v.x), "=r"(v.y), "=r"(v.z), "=r"(v.w) : "r"(a) : "memory");
  return v;
}
__device__ __forceinline__ float ldsf(uint32_t a) {
  float v;
  asm volatile("ld.shared.f32 %0, [%1];" : "=f"(v) : "r"(a) : "memory");
  return v;
}
__device__ __forceinline__ void stsf(uint32_t a, float v) {
  asm volatile("st.shared.f32 [%0], %1;" ::"r"(a), "f"(v) : "memory");
}
__device__ __forceinline__ void sts32(uint32_t a, uint32_t v) {
  asm volatile("st.shared.u32 [%0], %1;" ::"r"(a), "r"(v) : "memory");
}
__device__ __forceinline__ void sts16(uint32_t a, uint16_t v) {
  asm volatile("st.shared.u16 [%0], %1;" ::"r"(a), "h"(v) : "memory");
}
__device__ __forceinline__ float fsqrt_approx(float x) {
  float y;
  asm("sqrt.approx.f32 %0, %1;" : "=f"(y) : "f"(x));
  return y;
}
__device__ __forceinline__ float ex2(float x) {
  float y;
  asm("ex2.approx.ftz.f32 %0, %1;" : "=f"(y) : "f"(x));
  return y;
}
__device__ __forceinline__ int dep_zero(uint32_t r, uint32_t zero) { return (int)(r & zero); }
__device__ __forceinline__ void tma_issue(uint32_t dst, const CUtensorMap* tm, int c0, int row, uint32_t bar) {
  asm volatile(
      "{\n.reg .pred P;\nelect.sync _|P, 0xffffffff;\n"
      "@P mbarrier.arrive.expect_tx.shared::cta.b64 _, [%4], 2048;\n"
      "@P cp.async.bulk.tensor.2d.shared::cluster.global.tile.mbarrier::complete_tx::bytes.L2::cache_hint"
      " [%0], [%1, {%2, %3}], [%4], %5;\n}" ::"r"(dst), "l"(tm), "r"(c0), "r"(row), "r"(bar), "l"(POL_FIRST)
      : "memory");
}
__device__ __forceinline__ void tma_keep(const uint8_t* base, int row) {
  asm volatile(
      "{\n.reg .pred P;\nelect.sync _|P, 0xffffffff;\n"
      "@P cp.async.bulk.prefetch.L2.global.L2::cache_hint [%0], 2048, %1;\n}" ::"l"(base + (size_t)(uint32_t)row * 128),
      "l"(POL_NORMAL)
      : "memory");
}
__device__ __forceinline__ void tma_issue2(uint32_t dst, const CUtensorMap* tmK, const CUtensorMap* tmV, int c0, int row,
                                           uint32_t bar) {
  asm volatile(
      "{\n.reg .pred P;\nelect.sync _|P, 0xffffffff;\n"
      "@P mbarrier.arrive.expect_tx.shared::cta.b64 _, [%5], 4096;\n"
      "@P cp.async.bulk.tensor.2d.shared::cluster.global.tile.mbarrier::complete_tx::bytes.L2::cache_hint"
      " [%0], [%1, {%3, %4}], [%5], %6;\n"
      "@P cp.async.bulk.tensor.2d.shared::cluster.global.tile.mbarrier::complete_tx::bytes.L2::cache_hint"
      " [%7], [%2, {%3, %4}], [%5], %6;\n}" ::"r"(dst), "l"(tmK), "l"(tmV), "r"(c0), "r"(row), "r"(bar), "l"(POL_FIRST),
      "r"(dst + 2048)
      : "memory");
}
__device__ __forceinline__ uint32_t uni(uint32_t v) { return __shfl_sync(0xffffffffu, v, 0); }
__device__ __forceinline__ uint32_t ticket_take(uint32_t addr) {
  uint32_t v = 0;
  asm volatile("{\n.reg .pred P;\nelect.sync _|P, 0xffffffff;\n@P atom.shared.add.u32 %0, [%1], 1;\n}"
               : "+r"(v) : "r"(addr) : "memory");
  return v;
}
__device__ __forceinline__ uint32_t ticket_bcast(uint32_t v) { return __reduce_max_sync(0xffffffffu, v); }
__device__ __forceinline__ uint32_t pack_bf16(float lo, float hi) {
  uint32_t r;
  asm("cvt.rn.bf16x2.f32 %0, %1, %2;" : "=r"(r) : "f"(hi), "f"(lo));
  return r;
}
__device__ __forceinline__ float bf16r(float x) { return __uint_as_float(pack_bf16(0.f, x) & 0xffff0000u); }
__device__ __forceinline__ float bflo(uint32_t w) { return __uint_as_float(w << 16); }
__device__ __forceinline__ float bfhi(uint32_t w) { return __uint_as_float(w & 0xffff0000u); }

__device__ __forceinline__ uint32_t ll_tag(uint32_t epoch, uint32_t stage) { return 1 + (epoch * 3 + stage) % 255; }
__device__ __forceinline__ float ll_trunc(float v) { return __uint_as_float(__float_as_uint(v) & 0xffffff00u); }
__device__ __forceinline__ void ll_st(uint32_t* p, float v, uint32_t tag) {
  asm volatile("st.relaxed.gpu.global.u32 [%0], %1;" ::"l"(p), "r"((__float_as_uint(v) & 0xffffff00u) | tag) : "memory");
}
__device__ __forceinline__ void aux_sync() { asm volatile("bar.sync 1, 128;" ::: "memory"); }

struct Acc { float o0, o1, o2, o3, m, l; };

__device__ __forceinline__ uint32_t softmax8(float s0, float s1, float s2, float s3, Acc& a, int lane) {
  const float sc = ((lane & 16) ? (s1 + s2) : (s0 + s3)) * SCALE_LOG2;
  if (__any_sync(0xffffffffu, sc > a.m)) {
    float mx = fmaxf(sc, __shfl_xor_sync(0xffffffffu, sc, 4));
    mx = fmaxf(mx, __shfl_xor_sync(0xffffffffu, mx, 8));
    mx = fmaxf(mx, __shfl_xor_sync(0xffffffffu, mx, 16));
    mx = fmaxf(mx, a.m);
    const float alpha = ex2(a.m - mx);
    a.o0 *= alpha; a.o1 *= alpha; a.o2 *= alpha; a.o3 *= alpha; a.l *= alpha;
    a.m = mx;
  }
  const float p = ex2(sc - a.m);
  a.l += p;
  uint32_t pp, pk;
  asm("cvt.rn.bf16x2.f32 %0, %1, %1;" : "=r"(pp) : "f"(p));
  asm volatile("movmatrix.sync.aligned.m8n8.trans.b16 %0, %1;" : "=r"(pk) : "r"(pp));
  return pk;
}
__device__ __forceinline__ uint32_t qk_reg(const uint32_t* kf, uint32_t qaddr, Acc& a, int lane) {
  float s0 = 0.f, s1 = 0.f, s2 = 0.f, s3 = 0.f;
  {
    const uint4 q = lds128(qaddr);
    mma16816(s0, s1, s2, s3, kf + 0, q.x, q.y);
    mma16816(s0, s1, s2, s3, kf + 4, q.z, q.w);
  }
  {
    const uint4 q = lds128(qaddr + 128);
    mma16816(s0, s1, s2, s3, kf + 8, q.x, q.y);
    mma16816(s0, s1, s2, s3, kf + 12, q.z, q.w);
  }
  return softmax8(s0, s1, s2, s3, a, lane);
}
__device__ __forceinline__ void pv_q(const uint32_t* vf, int j, uint32_t pk, Acc& a, int lane) {
  const int g = lane >> 2;
  const bool cm = ((g & 1) == 0) == ((lane & 2) == 0);
  const bool mine = (g >> 1) == j;
  mma16816(a.o0, a.o1, a.o2, a.o3, vf, (mine && cm) ? pk : 0u, (mine && !cm) ? pk : 0u);
}
__device__ __forceinline__ void pv_reg(const uint32_t* vf, uint32_t pk, Acc& a, int lane) {
#pragma unroll
  for (int j = 0; j < 4; j++) pv_q(vf + 4 * j, j, pk, a, lane);
}


__device__ __forceinline__ void side_fill_w(const CUtensorMap* tmK, const CUtensorMap* tmV, uint32_t sb, uint32_t side,
                                            uint32_t wp, int lane, uint32_t i, uint32_t b, int dep) {
  const uint4 p = lds128(wp + 16);
  const uint32_t slot = uni((p.z & 255) + i * ((p.z >> 8) & 255));
  const int row = (int)(p.y + i * ((p.z >> 16) & 255) + b * TPB) * 16;
  tma_issue2(side + slot * 4096, tmK, tmV, dep, row, sb + OFF_SBAR + slot * 8);
}
__device__ __forceinline__ void stream_prologue(const CUtensorMap* tmK, const CUtensorMap* tmV, const uint32_t sb,
                                                const uint32_t side, const int w, const int lane) {
  const uint32_t ring = sb + OFF_RING + w * RING_W;
  const uint32_t rbar = sb + OFF_RBAR + w * 32;
  const uint32_t wp = sb + OFF_WP + w * 32;
  const uint4 p = lds128(wp + 16);
  const uint32_t nside = p.z >> 24;
  if (lane == 0) {
    mbar_expect_tx(rbar, 2048);      tma_load(ring, tmK, 0, (int)p.w * 16, rbar);
    mbar_expect_tx(rbar + 8, 2048);  tma_load(ring + 2048, tmV, 0, (int)p.w * 16, rbar + 8);
    mbar_expect_tx(rbar + 16, 2048); tma_load(ring + 4096, tmK, 0, (int)(p.w + 1) * 16, rbar + 16);
  }
  __syncwarp();
  side_fill_w(tmK, tmV, sb, side, wp, lane, 0, 0, 0);
  uint32_t sis = 1;
  if (nside > 1) side_fill_w(tmK, tmV, sb, side, wp, lane, sis++, 0, 0);
  int it = 0;
  while (!__all_sync(0xffffffffu, mbar_test(sb + BAR_Q1, 0))) {
    if (sis < nside &&
        __all_sync(0xffffffffu, mbar_test(sb + OFF_SBAR + ((p.z & 255) + (sis - 2) * ((p.z >> 8) & 255)) * 8, 0)))
      side_fill_w(tmK, tmV, sb, side, wp, lane, sis++, 0, 0);
    else
      __nanosleep(40);
    if (++it > SPIN_LIMIT) __trap();
  }
  if (lane == 0) sts32(sb + OFF_HELD + w * 4, sis);
  __syncwarp();
}

__device__ __forceinline__ void stream_warp(const CUtensorMap* tmK, const CUtensorMap* tmV, const uint32_t sb,
                                            const uint32_t side, const int w, const int lane, const Params& prm) {
  const uint32_t& zero = prm.zero;
  const uint32_t ring = sb + OFF_RING + w * RING_W;
  const uint32_t rbar = sb + OFF_RBAR + w * 32;
  const uint32_t wp = sb + OFF_WP + w * 32;
  uint32_t laneK, laneV;
  {
    const int mat = lane >> 3, i = lane & 7;
    const int hk = (mat & 1) ? (i < 4) : (i >= 4);
    const int rk = 2 * i + hk;
    laneK = ring + rk * 128 + (((mat >> 1) ^ (rk & 7)) << 4);
    laneV = laneK ^ (((mat ^ (mat >> 1)) & 1) << 7);
  }
  const uint32_t qoff = lds128(wp + 16).x + (((lane >> 2) & 1) * 4 + (lane & 3)) * 16;

  uint32_t kv[RP][32];
  Acc cur, oth;
  cur.o0 = cur.o1 = cur.o2 = cur.o3 = cur.l = 0.f; cur.m = -INFINITY;
  oth = cur;
  uint32_t st = 0;
  uint32_t csp = 0;
  uint32_t d0, d1;
  uint32_t ev;
  uint32_t ss = 0;
  uint32_t mseg = lds32(wp);
  const uint32_t ctrM = lds32(wp + 4);
  uint32_t tn = ticket_take(ctrM);

  auto ensure = [&](uint32_t b) {
    const uint32_t sw = b ^ ((st >> 11) & 1);
    static_assert(ST_CURB == 1u << 11, "");
    asm volatile(
        "{\n.reg .pred p;\n.reg .f32 t;\nsetp.eq.u32 p, %12, 0;\n@p bra.uni SKIP;\n"
        "mov.f32 t, %0;\nmov.f32 %0, %6;\nmov.f32 %6, t;\nmov.f32 t, %1;\nmov.f32 %1, %7;\nmov.f32 %7, t;\n"
        "mov.f32 t, %2;\nmov.f32 %2, %8;\nmov.f32 %8, t;\nmov.f32 t, %3;\nmov.f32 %3, %9;\nmov.f32 %9, t;\n"
        "mov.f32 t, %4;\nmov.f32 %4, %10;\nmov.f32 %10, t;\nmov.f32 t, %5;\nmov.f32 %5, %11;\nmov.f32 %11, t;\n"
        "SKIP:\n}"
        : "+f"(cur.o0), "+f"(cur.o1), "+f"(cur.o2), "+f"(cur.o3), "+f"(cur.m), "+f"(cur.l), "+f"(oth.o0), "+f"(oth.o1),
          "+f"(oth.o2), "+f"(oth.o3), "+f"(oth.m), "+f"(oth.l)
        : "r"(sw));
    st ^= sw << 11;
  };
  auto gate = [&](uint32_t b) {
    const uint32_t bit = b ? ST_R1 : ST_R0;
    if (!(st & bit)) { mbar_wait(sb + (b ? BAR_R1 : BAR_R0), 0); st |= bit; }
  };
  auto issue = [&](const CUtensorMap* tm, uint32_t dst, uint32_t bar, uint32_t d, int dep) {
    const int row = (int)(d & D_TILE) * 16;
    tma_issue(dst, tm, dep, row, bar);
    if (d & D_PF) tma_keep(tm == tmK ? prm.kbytes : prm.vbytes, row);
  };
  auto advance = [&]() {
    csp += 2048;
    if ((csp & 0x1800) == 0x1800) csp = (csp & 1) ^ 1;
  };
  auto reg_desc = [&](uint32_t i) { return D_VALID | D_REG | D_B1 | D_PAST0 | (lds128(wp + 16).w + TPB + i); };
  auto grab = [&]() -> uint32_t {
    const uint4 P = lds128(mseg);
    const uint32_t t = ticket_bcast(tn);
    uint32_t d;
    bool held = false;
    if (t < P.x) {
      d = P.y + t;
      if (t >= P.z) d |= D_PF;
    } else {
      const uint32_t s0 = lds32(wp);
      while (true) {
        const uint32_t si = (mseg - s0) >> 4;
        if (si >= 6) { d = D_PASTS | D_END; break; }
        const uint4 M = lds128(mseg);
        if (t < M.x) { d = (M.y + t) | (t >= M.z ? D_PF : 0u); break; }
        if (si == 3 && !(st & ST_INJ)) {
          st = (st | ST_INJ | ST_INJ2) & ~ST_SONLY;
          ev |= D_VALID;
          held = true;
          d = reg_desc(0);
          break;
        }
        mseg += 16;
      }
    }
    if (held) tn = t; else tn = ticket_take(ctrM);
    return d;
  };
  auto qk_smem = [&](Acc& A, uint32_t la, uint32_t qa, auto mid) -> uint32_t {
    float s0 = 0.f, s1 = 0.f, s2 = 0.f, s3 = 0.f;
    uint32_t f[8];
    ldsm4(f, la); ldsm4(f + 4, la ^ 32);
    {
      const uint4 q = lds128(qa);
      mma16816v(s0, s1, s2, s3, f, q.x, q.y);
      mma16816v(s0, s1, s2, s3, f + 4, q.z, q.w);
    }
    ldsm4(f, la ^ 64); ldsm4(f + 4, la ^ 96);
    mid(f[7]);
    {
      const uint4 q = lds128(qa + 128);
      mma16816v(s0, s1, s2, s3, f, q.x, q.y);
      mma16816v(s0, s1, s2, s3, f + 4, q.z, q.w);
    }
    return softmax8(s0, s1, s2, s3, A, lane);
  };
  auto pv_smem = [&](Acc& A, uint32_t la, uint32_t pk, auto mid) {
    const int g = lane >> 2;
    const bool cm = ((g & 1) == 0) == ((lane & 2) == 0);
    const uint32_t b0 = cm ? pk : 0u, b1 = cm ? 0u : pk;
    uint32_t f[8];
    ldsm4t(f, la); ldsm4t(f + 4, la ^ 32);
    mma16816v(A.o0, A.o1, A.o2, A.o3, f, (g >> 1) == 0 ? b0 : 0u, (g >> 1) == 0 ? b1 : 0u);
    mma16816v(A.o0, A.o1, A.o2, A.o3, f + 4, (g >> 1) == 1 ? b0 : 0u, (g >> 1) == 1 ? b1 : 0u);
    ldsm4t(f, la ^ 64); ldsm4t(f + 4, la ^ 96);
    mid(f[7]);
    mma16816v(A.o0, A.o1, A.o2, A.o3, f, (g >> 1) == 2 ? b0 : 0u, (g >> 1) == 2 ? b1 : 0u);
    mma16816v(A.o0, A.o1, A.o2, A.o3, f + 4, (g >> 1) == 3 ? b0 : 0u, (g >> 1) == 3 ? b1 : 0u);
  };
  auto ring_step = [&](const uint32_t d2) {
    csp = uni(csp);
    uint32_t so = csp & 0x1800, bar = rbar + (csp >> 8);
    mbar_wait(bar, csp & 1);
    const uint32_t pk = qk_smem(cur, laneK + so, qoff + ((d0 >> 8) & 256), [&](uint32_t last) {
      if (d1 & D_VALID) issue(tmV, ring + so, bar, d1, dep_zero(last, zero));
    });
    advance();
    so = csp & 0x1800; bar = rbar + (csp >> 8);
    mbar_wait(bar, csp & 1);
    pv_smem(cur, laneV + so, pk, [&](uint32_t last) {
      if (d2 & D_VALID) issue(tmK, ring + so, bar, d2, dep_zero(last, zero));
    });
    advance();
    d0 = d1; d1 = d2;
  };
  auto reg_step = [&](uint32_t* kf, uint32_t* vf, uint32_t b, bool staticNext, uint32_t dstatic) {
    const uint32_t d2 = staticNext ? dstatic : grab();
    csp = uni(csp);
    uint32_t so = csp & 0x1800, bar = rbar + (csp >> 8);
    mbar_wait(bar, csp & 1);
    {
      const uint32_t la = laneK + so;
      ldsm4(kf + 0, la); ldsm4(kf + 4, la ^ 32); ldsm4(kf + 8, la ^ 64); ldsm4(kf + 12, la ^ 96);
      if (d1 & D_VALID) issue(tmV, ring + so, bar, d1, dep_zero(kf[15], zero));
    }
    advance();
    const uint32_t pk = qk_reg(kf, qoff + b * 256, cur, lane);
    so = csp & 0x1800; bar = rbar + (csp >> 8);
    mbar_wait(bar, csp & 1);
    {
      const uint32_t la = laneV + so;
      ldsm4t(vf + 0, la); ldsm4t(vf + 4, la ^ 32); ldsm4t(vf + 8, la ^ 64); ldsm4t(vf + 12, la ^ 96);
      if (d2 & D_VALID) issue(tmK, ring + so, bar, d2, dep_zero(vf[15], zero));
    }
    pv_reg(vf, pk, cur, lane);
    advance();
    d0 = d1; d1 = d2;
  };
  auto flush = [&](uint32_t b, uint32_t area, uint32_t bar) {
    ensure(b);
    float l = cur.l;
    l += __shfl_xor_sync(0xffffffffu, l, 4);
    l += __shfl_xor_sync(0xffffffffu, l, 8);
    l += __shfl_xor_sync(0xffffffffu, l, 16);
    const uint32_t e = area + ((lane & 3) * 16 + (lane >> 2)) * 4;
    stsf(e, cur.o0); stsf(e + 256, cur.o1); stsf(e + 32, cur.o2); stsf(e + 288, cur.o3);
    if (lane == 0) { stsf(area + 512, cur.m); stsf(area + 516, l); }
    __syncwarp();
    if (lane == 0) mbar_arrive(bar);
    cur.o0 = cur.o1 = cur.o2 = cur.o3 = cur.l = 0.f; cur.m = -INFINITY;
  };
  auto side_fill = [&](uint32_t i, uint32_t b, int dep) { side_fill_w(tmK, tmV, sb, side, wp, lane, i, b, dep); };
  const uint32_t pzu = uni(lds128(wp + 16).z), kblk = uni(lds32(wp) + 112);
  auto side_try = [&](const uint32_t j, const bool force) -> bool {
    const uint32_t bit = 1u << j;
    const uint32_t slot = (pzu & 255) + j * ((pzu >> 8) & 255);
    const uint32_t bar = sb + OFF_SBAR + slot * 8;
    const uint32_t b = (ss >> (SS_B + j)) & 1;
    bool cyc;
    if (ss & (bit << SS_F)) {
      const uint32_t par = (ss >> (SS_P + j)) & 1;
      if (force) mbar_wait(bar, par);
      else if (!__all_sync(0xffffffffu, mbar_test(bar, par))) return false;
      cyc = (ss & (bit << SS_K)) != 0;
      ss ^= (bit << SS_F) | (bit << SS_P);
    } else {
      if (!(st & (b ? ST_R1 : ST_R0))) {
        if (!force) return false;
        gate(b);
      }
      cyc = true;
      ss &= ~((bit << SS_H0) | (bit << SS_H1));
    }
    const uint4 kb = lds128(kblk);
    uint32_t u = 0;
    if (cyc) u = ticket_take(kb.w + b * 32);
    const uint32_t delta = side + slot * 4096 - ring;
    auto next_load = [&](uint32_t last) {
      if (cyc) {
        u = ticket_bcast(u);
        const int dep = dep_zero(last, zero);
        if (u < kb.x) {
          const int row = (int)(kb.y + b * TPB - u) * 16;
          tma_issue2(ring + delta, tmK, tmV, dep, row, bar);
          ss |= (bit << SS_F) | (bit << SS_K);
        } else if (!b) {
          side_fill(j, 1, dep);
          ss = (ss & ~(bit << SS_K)) | (bit << SS_F) | (bit << SS_B);
        } else {
          ss &= ~(bit << SS_K);
        }
      } else {
        ss |= bit << (b ? SS_H1 : SS_H0);
      }
    };
    if (b == ((st & ST_CURB) ? 1u : 0u)) {
      const uint32_t pk = qk_smem(cur, laneK + delta, qoff + b * 256, [&](uint32_t) {});
      pv_smem(cur, laneV + delta + 2048, pk, next_load);
    } else {
      const uint32_t pk = qk_smem(oth, laneK + delta, qoff + b * 256, [&](uint32_t) {});
      pv_smem(oth, laneV + delta + 2048, pk, next_load);
    }
    return true;
  };

  ev = 0;
  uint32_t sfull;
  {
    const uint4 p = lds128(wp + 16);
    const uint32_t nside = p.z >> 24;
    sfull = (1u << nside) - 1;
    ss = sfull << SS_F;
    uint32_t sis = lds32(sb + OFF_HELD + w * 4);
    d0 = D_VALID | D_REG | D_B0 | p.w;
    d1 = D_VALID | D_REG | D_B0 | (p.w + 1);
#pragma unroll
    for (int i = 0; i < RP; i++) {
      if (sis < nside) side_fill(sis++, 0, 0);
      reg_step(&kv[i][0], &kv[i][16], 0, i + 2 < RP, D_VALID | D_REG | D_B0 | (lds128(wp + 16).w + i + 2));
    }
    while (sis < nside) side_fill(sis++, 0, 0);
  }
  ev = D_VALID | D_END;
  while (true) {
    uint32_t d2;
    if (d0 & ev) {
      if ((d0 & ev & ~(D_B0 | D_B1)) == 0) {
        ensure((d0 >> 16) & 1);
        ev ^= D_B0 | D_B1;
        d2 = grab();
      } else {
        const bool sonly = (d0 & ev & ~D_VALID) == 0 && (st & ST_SONLY);
        if (sonly) {
        } else if (!(st & ST_R0)) {
          if ((st & ST_FL0) && __all_sync(0xffffffffu, mbar_test(sb + BAR_R0, 0))) st |= ST_R0;
        } else if (!(st & ST_R1)) {
          if ((st & ST_FL1) && __all_sync(0xffffffffu, mbar_test(sb + BAR_R1, 0))) st |= ST_R1;
        }
        {
          const uint32_t sF = (ss >> SS_F) & 31, sH0 = (ss >> SS_H0) & 31, sH1 = (ss >> SS_H1) & 31;
          uint32_t need = 0;
          if (sonly) {}
          else if (!(st & ST_FL0)) { if (d0 & D_PAST0) need = sF; }
          else if (!(st & ST_FL1)) { if (d0 & D_PAST1) need = sfull & ~sH1; }
          else if (d0 & D_END) need = sF | sH0 | sH1;
          const bool force = need != 0;
          uint32_t cand = force ? need : (sF | ((st & ST_R0) ? sH0 : 0u) | ((st & ST_R1) ? sH1 : 0u));
          while (cand) {
            const uint32_t j = __ffs(cand) - 1;
            cand &= cand - 1;
            if (side_try(j, force)) break;
          }
          if (force) { ev |= D_VALID | D_END; st &= ~ST_SONLY; continue; }
        }
        if (sonly) {
          const uint32_t act = (ss >> SS_F) | ((st & ST_R0) ? (ss >> SS_H0) : 0u) | ((st & ST_R1) ? (ss >> SS_H1) : 0u);
          if (!(act & 31)) { ev &= ~D_VALID; st &= ~ST_SONLY; }
          d2 = grab();
          goto step;
        }
        {
        bool redo = true;
        if (!(st & ST_FL0) && (d0 & D_PAST0)) {
          flush(0, sb + OFF_PART + w * 528, sb + BAR_P0);
          st |= ST_FL0;
        } else if (d0 & D_REG) {
          gate(0);
#pragma unroll
          for (int i = 0; i < RP; i++) {
            if (i == 0) ensure(1);
            const uint32_t pk = qk_reg(&kv[i][0], qoff, oth, lane);
            pv_reg(&kv[i][16], pk, oth, lane);
            reg_step(&kv[i][0], &kv[i][16], 1, i + 2 < RP, reg_desc(i + 2));
          }
        } else if (!(st & ST_FL1) && (d0 & D_PAST1)) {
          flush(1, sb + OFF_PART + w * 528, sb + BAR_P0 + 8);
          st |= ST_FL1;
        } else if (!(st & ST_FL2) && (d0 & D_PAST2)) {
          gate(1);
          flush(0, sb + OFF_PART + w * 528, sb + BAR_P0 + 16);
          st |= ST_FL2;
        } else if (!(st & ST_REGC) && ((st & ST_R1) || (d0 & D_END))) {
          gate(1);
          ensure(1);
#pragma unroll
          for (int i = 0; i < RP; i++) {
            const uint32_t pk = qk_reg(&kv[i][0], qoff + 256, cur, lane);
            pv_reg(&kv[i][16], pk, cur, lane);
          }
          st |= ST_REGC;
        } else if (d0 & D_END) {
          break;
        } else {
          redo = false;
        }
        if (redo) { ev |= D_VALID | D_END; st &= ~ST_SONLY; continue; }
        if (d0 & D_N0) gate(0);
        if (d0 & D_N1) gate(1);
        ensure((d0 >> 16) & 1);
        bool forced = false;
        if (st & ST_INJ2) {
          st &= ~ST_INJ2;
          d2 = reg_desc(1);
          forced = true;
        } else if ((st & (ST_R0 | ST_INJ)) == ST_R0) {
          st |= ST_INJ | ST_INJ2;
          d2 = reg_desc(0);
          forced = true;
        }
        ev = D_REG | D_END | ((st & ST_CURB) ? D_B0 : D_B1) | ((st & ST_FL0) ? 0u : D_PAST0) |
             ((st & ST_FL1) ? 0u : D_PAST1) | ((st & ST_FL2) ? 0u : D_PAST2) | ((st & ST_R0) ? 0u : D_N0) |
             ((st & ST_R1) ? 0u : D_N1);
        const uint32_t act = (ss >> SS_F) | ((st & ST_R0) ? (ss >> SS_H0) : 0u) | ((st & ST_R1) ? (ss >> SS_H1) : 0u);
        st &= ~ST_SONLY;
        if ((st & ST_INJ2) || ((st & (ST_R1 | ST_REGC)) == ST_R1)) ev |= D_VALID;
        else if (act & 31) { ev |= D_VALID; st |= ST_SONLY; }
        if (((st & ST_FL0) && !(st & ST_R0)) || ((st & ST_FL1) && !(st & ST_R1))) ev |= 1;
        if (!forced) d2 = grab();
        }
      }
    } else {
      d2 = grab();
    }
  step:
    ring_step(d2);
  }
  flush(1, ring, sb + BAR_P0 + 24);
}

__device__ __forceinline__ void aux_layernorm(const uint32_t sb, const uint32_t dst, const int t, float x0, float x1,
                                              float x2, float x3) {
  float s = (x0 + x1) + (x2 + x3);
#pragma unroll
  for (int o = 16; o; o >>= 1) s += __shfl_xor_sync(0xffffffffu, s, o);
  const float mw = s * (1.f / 128);
  float v = ((x0 - mw) * (x0 - mw) + (x1 - mw) * (x1 - mw)) + ((x2 - mw) * (x2 - mw) + (x3 - mw) * (x3 - mw));
#pragma unroll
  for (int o = 16; o; o >>= 1) v += __shfl_xor_sync(0xffffffffu, v, o);
  if ((t & 31) == 0) { stsf(sb + OFF_RED + (t >> 5) * 4, mw); stsf(sb + OFF_RED + 16 + (t >> 5) * 4, v); }
  aux_sync();
  const uint4 rs = lds128(sb + OFF_RED), rv = lds128(sb + OFF_RED + 16);
  const float m0 = __uint_as_float(rs.x), m1 = __uint_as_float(rs.y), m2 = __uint_as_float(rs.z), m3 = __uint_as_float(rs.w);
  const float mean = ((m0 + m1) + (m2 + m3)) * 0.25f;
  const float var = (((__uint_as_float(rv.x) + __uint_as_float(rv.y)) + (__uint_as_float(rv.z) + __uint_as_float(rv.w))) +
                     128.f * (((m0 - mean) * (m0 - mean) + (m1 - mean) * (m1 - mean)) +
                              ((m2 - mean) * (m2 - mean) + (m3 - mean) * (m3 - mean)))) * (1.f / DM);
  const float m = bf16r(mean);
  const float den = bf16r(fsqrt_approx(bf16r(bf16r(var) + 1e-5f)));
  sts32(dst + t * 8, pack_bf16(__fdividef(bf16r(x0 - m), den), __fdividef(bf16r(x1 - m), den)));
  sts32(dst + t * 8 + 4, pack_bf16(__fdividef(bf16r(x2 - m), den), __fdividef(bf16r(x3 - m), den)));
  aux_sync();
}
__device__ __forceinline__ void cp16(uint32_t dst, const void* src) {
  asm volatile("cp.async.cg.shared.global.L2::cache_hint [%0], [%1], 16, %2;" ::"r"(dst), "l"(src), "l"(POL_FIRST) : "memory");
}
__device__ __forceinline__ void cp16_shared(uint32_t dst, const void* src) {
  asm volatile("cp.async.cg.shared.global [%0], [%1], 16;" ::"r"(dst), "l"(src) : "memory");
}
__device__ __forceinline__ void cp_wait_all() { asm volatile("cp.async.wait_all;" ::: "memory"); }
__device__ __forceinline__ void gemv_mma(float& c0, float& c1, float& c2, float& c3, uint32_t la, uint32_t astep,
                                         uint32_t xa, int nk) {
  float e0 = 0.f, e1 = 0.f, e2 = 0.f, e3 = 0.f;
#pragma unroll 1
  for (int k = 0; k < nk; k += 2) {
    uint32_t a[4], a2[4];
    ldsm4t(a, la);
    ldsm4t(a2, la + astep);
    const uint32_t b0 = lds32(xa), b1 = lds32(xa + 16), b2 = lds32(xa + 32), b3 = lds32(xa + 48);
    mma16816(c0, c1, c2, c3, a, b0, b1);
    mma16816(e0, e1, e2, e3, a2, b2, b3);
    la += 2 * astep;
    xa += 64;
  }
  c0 += e0; c1 += e1; c2 += e2; c3 += e3;
}
__device__ __forceinline__ void gemv2_mma(float& c0, float& c2, float& e0, float& e2, uint32_t la, uint32_t lb, uint32_t astep,
                                          uint32_t xa, int nk) {
  float c1 = 0.f, c3 = 0.f, e1 = 0.f, e3 = 0.f;
  c0 = c2 = e0 = e2 = 0.f;
#pragma unroll 2
  for (int k = 0; k < nk; k++) {
    uint32_t a[4], a2[4];
    ldsm4t(a, la);
    ldsm4t(a2, lb);
    const uint32_t b0 = lds32(xa), b1 = lds32(xa + 16);
    mma16816(c0, c1, c2, c3, a, b0, b1);
    mma16816(e0, e1, e2, e3, a2, b0, b1);
    la += astep; lb += astep;
    xa += 32;
  }
}
__device__ __forceinline__ uint32_t ll_raw(const uint32_t* p) {
  uint32_t w;
  asm volatile("ld.relaxed.gpu.global.u32 %0, [%1];" : "=r"(w) : "l"(p) : "memory");
  return w;
}
__device__ __forceinline__ uint2 ll_raw2(const uint32_t* p) {
  uint2 w;
  asm volatile("ld.relaxed.gpu.global.v2.u32 {%0,%1}, [%2];" : "=r"(w.x), "=r"(w.y) : "l"(p) : "memory");
  return w;
}
__device__ __forceinline__ bool ll_ok(uint32_t w, uint32_t tag) { return (w & 255) == tag; }
__device__ __forceinline__ float ll_val(uint32_t w) { return __uint_as_float(w & 0xffffff00u); }
__device__ __forceinline__ void ll_backoff(int& it) {
  if (++it > SPIN_LIMIT) __trap();
  __nanosleep(40);
}
__device__ __forceinline__ float ll_wait1(const uint32_t* p, uint32_t tag) {
  int it = 0;
  while (true) {
    const uint32_t w = ll_raw(p);
    if (ll_ok(w, tag)) return ll_val(w);
    ll_backoff(it);
  }
}
__device__ __forceinline__ void ll_wait4(const uint32_t* p, uint32_t tag, float& x0, float& x1, float& x2, float& x3) {
  int it = 0;
  while (true) {
    uint32_t a, b, c, d;
    asm volatile("ld.relaxed.gpu.global.v4.u32 {%0,%1,%2,%3}, [%4];" : "=r"(a), "=r"(b), "=r"(c), "=r"(d) : "l"(p) : "memory");
    if (ll_ok(a, tag) && ll_ok(b, tag) && ll_ok(c, tag) && ll_ok(d, tag)) {
      x0 = ll_val(a); x1 = ll_val(b); x2 = ll_val(c); x3 = ll_val(d);
      return;
    }
    ll_backoff(it);
  }
}
__device__ __forceinline__ void ll_wait2s(const uint32_t* p, int stride, uint32_t tag, float& x0, float& x1) {
  int it = 0;
  while (true) {
    const uint32_t a = ll_raw(p), b = ll_raw(p + stride);
    if (ll_ok(a, tag) && ll_ok(b, tag)) { x0 = ll_val(a); x1 = ll_val(b); return; }
    ll_backoff(it);
  }
}
__device__ __forceinline__ float warp_sum4(float v0, float v1, float v2, float v3, int lane) {
  const bool h16 = lane & 16, h8 = lane & 8;
  const float k0 = (h16 ? v2 : v0) + __shfl_xor_sync(0xffffffffu, h16 ? v0 : v2, 16);
  const float k1 = (h16 ? v3 : v1) + __shfl_xor_sync(0xffffffffu, h16 ? v1 : v3, 16);
  float k = (h8 ? k1 : k0) + __shfl_xor_sync(0xffffffffu, h8 ? k0 : k1, 8);
  k += __shfl_xor_sync(0xffffffffu, k, 4);
  k += __shfl_xor_sync(0xffffffffu, k, 2);
  k += __shfl_xor_sync(0xffffffffu, k, 1);
  return k;
}
__device__ __forceinline__ void hint_arrive(unsigned int* c, const int t) {
  aux_sync();
  if (t == 0) asm volatile("red.relaxed.gpu.global.add.u32 [%0], 1;" ::"l"(c) : "memory");
}
__device__ __forceinline__ void hint_wait(const unsigned int* c, uint32_t target, const int t) {
  if (t == 0) {
    int it = 0;
    while (true) {
      uint32_t v;
      asm volatile("ld.relaxed.gpu.global.u32 %0, [%1];" : "=r"(v) : "l"(c) : "memory");
      if ((int)(v - target) >= 0) break;
      if (++it > SPIN_LIMIT) __trap();
      __nanosleep(20);
    }
  }
  aux_sync();
}
__device__ __forceinline__ void aux_qproj(const uint32_t sb, const int t, int h, int r, uint32_t xn0, uint32_t xn1, int b0,
                                          int nb, uint32_t tag) {
  const int wq = t >> 5, lane = t & 31, mat = lane >> 3, g = lane >> 2;
  const int row = (wq >> 1) * 256 + (mat >> 1) * 8 + (lane & 7), ch = 2 * (wq & 1) + (mat & 1);
  float c0 = 0.f, c1 = 0.f, c2 = 0.f, c3 = 0.f;
  gemv_mma(c0, c1, c2, c3, sb + OFF_WQ + row * 64 + ((ch ^ ((row >> 1) & 3)) << 4), 1024,
           ((g & 1) ? xn1 : xn0) + ((wq >> 1) * 256 + 2 * (lane & 3)) * 2, 16);
  if ((lane & 3) == 0) {
    const uint32_t e = sb + SC_RED4 + ((wq >> 1) * 64 + (wq & 1) * 16 + g) * 4;
    stsf(e, c0); stsf(e + 32, c2); stsf(e + 128, c1); stsf(e + 160, c3);
  }
  aux_sync();
  if (t < 32 * nb)
    ll_st(&g_Q[b0 + (t >> 5)][h][r * 32 + (t & 31)], bf16r(ldsf(sb + SC_RED4 + t * 4) + ldsf(sb + SC_RED4 + (64 + t) * 4)), tag);
  aux_sync();
  if (t < nb) asm volatile("red.relaxed.gpu.global.add.u32 [%0], 1;" ::"l"(&g_cntQ[b0 + t][h]) : "memory");
}
__device__ __forceinline__ void qfrag_store(uint32_t qf, const int t, float q) {
  const int half = t >> 6, j = (t >> 4) & 3, k = t & 15;
  const uint32_t off = (j >> 1) * 128 + (half * 4 + ((k & 7) >> 1)) * 16 + ((j & 1) * 2 + (k >> 3)) * 4 + (k & 1) * 2;
  sts16(qf + off, (uint16_t)(__float_as_uint(q) >> 16));
}

__device__ __forceinline__ int aux_tid() {
  int t;
  asm volatile("mov.u32 %0, %%tid.x;" : "=r"(t));
  return t - 256;
}
#define AUX_STAGE() \
  t = aux_tid(); wq = t >> 5; lane = t & 31; mat = lane >> 3; g = lane >> 2; i8 = lane & 7

__device__ __forceinline__ void aux_chain(const Params& p, const uint32_t sb, const int c, const int b,
                                          const int layer, const uint32_t epoch, uint32_t area, uint32_t astride,
                                          uint32_t pbar) {
  const uint32_t tag = ll_tag(epoch, 1 + layer);
  const bool last = b && layer;
  const uint32_t use = 2 * (epoch - 1) + layer + 1;
  const int h = c >> 2, r = c & 3;
  int t, wq, lane, mat, g, i8;
  AUX_STAGE();
  const int nsrc = p.ht ? 5 : 4;
  mbar_wait(pbar, 0);
  {
    float M = -INFINITY;
#pragma unroll
    for (int k = 0; k < 8; k++) M = fmaxf(M, ldsf(area + k * astride + 512));
    M = ll_trunc(M);
    float O = 0.f, L = 0.f;
#pragma unroll 4
    for (int k = 0; k < 8; k++) {
      const float sc = ex2(ldsf(area + k * astride + 512) - M);
      O = fmaf(sc, ldsf(area + k * astride + t * 4), O);
      L = fmaf(sc, ldsf(area + k * astride + 516), L);
    }
    ll_st(&g_P[b][h][r][t], O, tag);
    if (t == 0) { ll_st(&g_P[b][h][r][128], M, tag); ll_st(&g_P[b][h][r][129], L, tag); }
  }
  hint_arrive(&g_cntP[b][h], t);
  hint_wait(&g_cntP[b][h], use * nsrc - (last ? 1 : 0), t);
  AUX_STAGE();
  {
    const uint32_t* P0 = &g_P[b][h][0][0];
    const int s4 = nsrc == 5 ? 528 : 0;
    uint32_t o0, o1, o2, o3, o4;
    uint2 q0, q1, q2, q3, q4;
    int it = 0;
    while (true) {
      o0 = ll_raw(P0 + t); o1 = ll_raw(P0 + 132 + t); o2 = ll_raw(P0 + 264 + t); o3 = ll_raw(P0 + 396 + t); o4 = ll_raw(P0 + s4 + t);
      q0 = ll_raw2(P0 + 128); q1 = ll_raw2(P0 + 260); q2 = ll_raw2(P0 + 392); q3 = ll_raw2(P0 + 524); q4 = ll_raw2(P0 + s4 + 128);
      const bool ok = ll_ok(o0, tag) && ll_ok(o1, tag) && ll_ok(o2, tag) && ll_ok(o3, tag) && ll_ok(o4, tag) &&
                      ll_ok(q0.x, tag) && ll_ok(q0.y, tag) && ll_ok(q1.x, tag) && ll_ok(q1.y, tag) && ll_ok(q2.x, tag) &&
                      ll_ok(q2.y, tag) && ll_ok(q3.x, tag) && ll_ok(q3.y, tag) && ll_ok(q4.x, tag) && ll_ok(q4.y, tag);
      if (ok) break;
      ll_backoff(it);
    }
    const float M = fmaxf(fmaxf(fmaxf(ll_val(q0.x), ll_val(q1.x)), fmaxf(ll_val(q2.x), ll_val(q3.x))), ll_val(q4.x));
    const float e0 = ex2(ll_val(q0.x) - M), e1 = ex2(ll_val(q1.x) - M), e2 = ex2(ll_val(q2.x) - M), e3 = ex2(ll_val(q3.x) - M);
    const float e4 = nsrc == 5 ? ex2(ll_val(q4.x) - M) : 0.f;
    const float L = (e0 * ll_val(q0.y) + e1 * ll_val(q1.y)) + (e2 * ll_val(q2.y) + e3 * ll_val(q3.y)) + e4 * ll_val(q4.y);
    const float o = __fdividef((e0 * ll_val(o0) + e1 * ll_val(o1)) + (e2 * ll_val(o2) + e3 * ll_val(o3)) + e4 * ll_val(o4), L);
    sts16(sb + SC_O + t * 2, (uint16_t)(pack_bf16(o, 0.f) & 0xffffu));
  }
  aux_sync();
  AUX_STAGE();
  {
    float c0, c2, e0, e2;
    const uint32_t rowa = sb + OFF_WO + ((mat >> 1) * 8 + i8) * 256;
    gemv2_mma(c0, c2, e0, e2, rowa + (((4 * wq + (mat & 1)) ^ i8) << 4), rowa + (((4 * wq + 2 + (mat & 1)) ^ i8) << 4), 4096,
              sb + SC_O + (lane & 3) * 4, 8);
    const float v = (lane & 2) ? ((lane & 1) ? e2 : e0) : ((lane & 1) ? c2 : c0);
    ll_st(&g_Z[b][h][r * 128 + (2 * wq + ((lane >> 1) & 1)) * 16 + g + 8 * (lane & 1)], v, tag);
  }
  hint_arrive(&g_cntZ[b][r], t);
  AUX_STAGE();
  hint_wait(&g_cntZ[b][c >> 5], use * NH - (last ? 4 : 0), t);
  if (wq == 0) {
    float z0, z1, z2, z3;
    ll_wait4(&g_Z[b][lane][4 * c], tag, z0, z1, z2, z3);
    __syncwarp();
    const float xres = bf16r(ldsf(sb + OFF_XRES + (b * 4 + mat) * 4) + bf16r(warp_sum4(z0, z1, z2, z3, lane)));
    __syncwarp();
    if (i8 == 0) {
      stsf(sb + OFF_XRES + (b * 4 + mat) * 4, xres);
      ll_st(&g_X1[b][4 * c + mat], xres, tag);
    }
  }
  hint_arrive(&g_cntX1[b], t);
  AUX_STAGE();
  const int ng = ffn_groups(c);
  {
    float x0, x1, x2, x3;
    if (!last) hint_wait(&g_cntX1[b], use * NMAIN, t);
    ll_wait4(&g_X1[b][4 * t], tag, x0, x1, x2, x3);
    aux_layernorm(sb, sb + OFF_XN, t, x0, x1, x2, x3);
  }
  AUX_STAGE();
  {
    const uint32_t la = sb + OFF_WF + (mat & 1) * 8192 + (wq * 128 + (mat >> 1) * 8 + i8) * 16;
    const uint32_t xa = sb + OFF_XN + (wq * 128 + 2 * (lane & 3)) * 2;
    float c0 = 0.f, c1 = 0.f, c2 = 0.f, c3 = 0.f, e0 = 0.f, e2 = 0.f;
    if (ng == 2) gemv2_mma(c0, c2, e0, e2, la, la + WF_BYTES, 256, xa, 8);
    else gemv_mma(c0, c1, c2, c3, la, 256, xa, 8);
    if ((lane & 3) == 0) {
      const uint32_t e = sb + SC_RED4 + (wq * 16 + g) * 4;
      stsf(e, c0); stsf(e + 32, c2);
      if (ng == 2) { stsf(e + 256, e0); stsf(e + 288, e2); }
    }
  }
  aux_sync();
  if (t < 8 * ng) {
    const uint32_t e = sb + SC_RED4 + ((t >> 3) * 64 + (t & 7)) * 4;
    const float gt = ldsf(e) + ldsf(e + 64) + ldsf(e + 128) + ldsf(e + 192);
    const float up = ldsf(e + 32) + ldsf(e + 96) + ldsf(e + 160) + ldsf(e + 224);
    ll_st(&g_H[b][((t >> 3) ? ffn_second(c) : c) * 8 + (t & 7)], bf16r(bf16r(gt) * bf16r(up)), tag);
  }
  hint_arrive(&g_cntD[b], t);
  AUX_STAGE();
  if (!last) hint_wait(&g_cntD[b], use * NMAIN, t);
  {
    const uint32_t* hp = &g_H[b][t];
    const bool has10 = t < FF - 1280;
    uint32_t hw[11];
    int it = 0;
    while (true) {
      bool ok = true;
#pragma unroll
      for (int i = 0; i < 10; i++) hw[i] = ll_raw(hp + 128 * i);
      hw[10] = has10 ? ll_raw(hp + 1280) : tag;
#pragma unroll
      for (int i = 0; i < 11; i++) ok = ok && ll_ok(hw[i], tag);
      if (ok) break;
      ll_backoff(it);
    }
    float d0 = 0.f, d1 = 0.f, d2 = 0.f, d3 = 0.f;
#pragma unroll
    for (int i = 0; i < 11; i++) {
      const uint2 v = lds64(sb + OFF_WD + (has10 || i < 10 ? t + 128 * i : t) * 8);
      const float hh = ll_val(hw[i]);
      d0 = fmaf(hh, bflo(v.x), d0); d1 = fmaf(hh, bfhi(v.x), d1);
      d2 = fmaf(hh, bflo(v.y), d2); d3 = fmaf(hh, bfhi(v.y), d3);
    }
    __syncwarp();
    const float d = warp_sum4(d0, d1, d2, d3, lane);
    if (i8 == 0) stsf(sb + SC_RED4 + (wq * 4 + mat) * 4, d);
    aux_sync();
    if (wq == 0) {
      const uint32_t e = sb + SC_RED4 + mat * 4;
      const float xres = bf16r(ldsf(sb + OFF_XRES + (b * 4 + mat) * 4) +
                               bf16r((ldsf(e) + ldsf(e + 16)) + (ldsf(e + 32) + ldsf(e + 48))));
      __syncwarp();
      if (i8 == 0) {
        stsf(sb + OFF_XRES + (b * 4 + mat) * 4, xres);
        if (layer == 0) ll_st(&g_X2[b][4 * c + mat], xres, tag);
        else p.out[b * DM + 4 * c + mat] = __float2bfloat16_rn(xres);
      }
    }
    if (layer == 0) hint_arrive(&g_cntX2[b], t);
  }
  AUX_STAGE();
  if (layer == 0) {
    {
      float x0, x1, x2, x3;
      hint_wait(&g_cntX2[b], epoch * NMAIN, t);
      ll_wait4(&g_X2[b][4 * t], tag, x0, x1, x2, x3);
      aux_layernorm(sb, sb + OFF_XN, t, x0, x1, x2, x3);
    }
    AUX_STAGE();
    aux_qproj(sb, t, h, r, sb + OFF_XN, sb + OFF_XN, b, 1, tag);
    AUX_STAGE();
    int bq;
    asm volatile("mov.u32 %0, %1;" : "=r"(bq) : "r"(b));
    hint_wait(&g_cntQ[bq][h], epoch * 8, t);
    qfrag_store(sb + OFF_QF + b * 256, t, ll_wait1(&g_Q[b][h][t], tag));
    aux_sync();
    if (t == 0) mbar_arrive(sb + (b ? BAR_R1 : BAR_R0));
  }
}

__device__ __forceinline__ void aux_fill_wq(const Params& p, const uint32_t sb, const int t, const int c) {
  const int h = c >> 2, r = c & 3;
#pragma unroll 4
  for (int i = 0; i < 16; i++) {
    const int row = i * 32 + (t >> 2), ch = t & 3;
    cp16(sb + OFF_WQ + row * 64 + ((ch ^ ((row >> 1) & 3)) << 4), p.wq + (size_t)row * (NH * 128) + h * 128 + r * 32 + ch * 8);
  }
}
__device__ __forceinline__ void aux_fill_rest(const Params& p, const uint32_t sb, const int t, const int c) {
  const int h = c >> 2, r = c & 3;
#pragma unroll 1
  for (int i = 0; i < 16; i++) {
    const int row = i * 8 + (t >> 4), ch = t & 15;
    cp16(sb + OFF_WO + row * 256 + ((ch ^ (row & 7)) << 4), p.wo + (size_t)(h * 128 + row) * DM + r * 128 + ch * 8);
    if ((i & 3) == 3) cp_wait_all();
  }
  const int ng = ffn_groups(c);
#pragma unroll 1
  for (int gi = 0; gi < ng; gi++) {
    const int G = gi ? ffn_second(c) : c;
    const uint32_t base = sb + OFF_WF + gi * WF_BYTES;
#pragma unroll 1
    for (int i = 0; i < 4; i++) {
      const int q = i * 128 + t;
      cp16_shared(base + q * 16, p.wg + (size_t)q * FF + G * 8);
      cp16_shared(base + 8192 + q * 16, p.wu + (size_t)q * FF + G * 8);
      if (i & 1) cp_wait_all();
    }
  }
#pragma unroll 1
  for (int f = t; f < FF; f += 128) {
    asm volatile("cp.async.ca.shared.global [%0], [%1], 8;" ::"r"(sb + OFF_WD + f * 8), "l"(p.wd + (size_t)f * DM + 4 * c)
                 : "memory");
    if ((f >> 7) % 4 == 3) cp_wait_all();
  }
  cp_wait_all();
  aux_sync();
}

__device__ __forceinline__ void aux_init_main(const Params& p, const uint32_t sb, const int t, const int c, const uint32_t tag) {
  const uint2 xa = *reinterpret_cast<const uint2*>(p.x + 4 * t);
  const uint2 xb = *reinterpret_cast<const uint2*>(p.x + DM + 4 * t);
  aux_layernorm(sb, sb + OFF_XN, t, bflo(xa.x), bfhi(xa.x), bflo(xa.y), bfhi(xa.y));
  aux_layernorm(sb, sb + SC_XN1, t, bflo(xb.x), bfhi(xb.x), bflo(xb.y), bfhi(xb.y));
  cp_wait_all();
  aux_sync();
  aux_qproj(sb, t, c >> 2, c & 3, sb + OFF_XN, sb + SC_XN1, 0, 2, tag);
}

__device__ __forceinline__ void aux_main(const Params& p, const uint32_t sb, const int t, const int c, const uint32_t epoch) {
  const int h = c >> 2;
  const uint32_t tag0 = ll_tag(epoch, 0);
  {
    float q0, q1;
    ll_wait2s(&g_Q[0][h][t], NH * 128, tag0, q0, q1);
    qfrag_store(sb + OFF_QF, t, q0);
    qfrag_store(sb + OFF_QF + 256, t, q1);
  }
  aux_sync();
  if (t == 0) mbar_arrive(sb + BAR_Q1);
  aux_fill_rest(p, sb, t, c);
  if (t < 8) stsf(sb + OFF_XRES + t * 4, __bfloat162float(p.x[(t >> 2) * DM + 4 * c + (t & 3)]));
  aux_sync();
#pragma unroll 1
  for (int k = 0; k < 4; k++) {
    const int b = k & 1, layer = k >> 1;
    aux_chain(p, sb, c, b, layer, epoch, k == 3 ? sb + OFF_RING : sb + OFF_PART, k == 3 ? RING_W : 528,
              sb + BAR_P0 + 8 * k);
  }
}

__device__ __forceinline__ void aux_helper(const uint32_t sb, const int t, const int j, const uint32_t epoch) {
  const uint32_t tag0 = ll_tag(epoch, 0), tag1 = ll_tag(epoch, 1), tag2 = ll_tag(epoch, 2);
  const uint32_t qf = sb + OFF_QF_HELP;
#pragma unroll 1
  for (int w = 0; w < 8; w++) {
    hint_wait(&g_cntQ[1][8 * j + w], epoch * 8 - 4, t);
    for (int b = 0; b < 2; b++) qfrag_store(qf + w * 512 + b * 256, t, ll_wait1(&g_Q[b][8 * j + w][t], tag0));
  }
  aux_sync();
  if (t == 0) mbar_arrive(sb + BAR_Q1);
#pragma unroll 1
  for (int k = 0; k < 4; k++) {
    const int b = k & 1, layer = k >> 1;
    const uint32_t tag = layer ? tag2 : tag1;
    const uint32_t area = k == 3 ? sb + OFF_RING : sb + OFF_PART, astride = k == 3 ? RING_W : 528;
    mbar_wait(sb + BAR_P0 + 8 * k, 0);
    for (int w = 0; w < 8; w++) {
      const float m = ldsf(area + w * astride + 512), mt = ll_trunc(m), sc = ex2(m - mt);
      ll_st(&g_P[b][8 * j + w][4][t], sc * ldsf(area + w * astride + t * 4), tag);
      if (t < 2) ll_st(&g_P[b][8 * j + w][4][128 + t], t ? sc * ldsf(area + w * astride + 516) : mt, tag);
    }
    aux_sync();
    if (t < 8) asm volatile("red.relaxed.gpu.global.add.u32 [%0], 1;" ::"l"(&g_cntP[b][8 * j + t]) : "memory");
    if (layer == 0) {
#pragma unroll 1
      for (int w = 0; w < 8; w++) {
        hint_wait(&g_cntQ[b][8 * j + w], epoch * 8, t);
        qfrag_store(qf + w * 512 + b * 256, t, ll_wait1(&g_Q[b][8 * j + w][t], tag1));
      }
      aux_sync();
      if (t == 0) mbar_arrive(sb + (b ? BAR_R1 : BAR_R0));
    }
  }
}

__global__ void __launch_bounds__(384, 1)
fused_decode_kernel(const __grid_constant__ CUtensorMap tmK, const __grid_constant__ CUtensorMap tmV,
                    const __grid_constant__ Params p) {
  extern __shared__ __align__(1024) uint8_t smem[];
  const uint32_t sb = (uint32_t)__cvta_generic_to_shared(smem);
  const int tid = threadIdx.x;
  const int w = __shfl_sync(0xffffffffu, tid >> 5, 0);
  const int lane = tid & 31;
  const int c = blockIdx.x;
  const bool helper = c >= NMAIN;

  const uint32_t side = sb + (helper ? OFF_W + 4096 : OFF_WF + ffn_groups(c) * WF_BYTES);
  if (w < 8) {
    if (lane == 0) {
      const int h = helper ? (c - NMAIN) * 8 + w : c >> 2, r = helper ? 4 : c & 3;
      const uint32_t q = helper ? p.q >> 3 : p.q;
      uint32_t own[5], total = 0, start = 0;
#pragma unroll
      for (int i = 0; i < 5; i++) {
        const uint32_t slots = (SMEM_BYTES - (OFF_WF + ffn_groups(4 * h + (i & 3)) * WF_BYTES)) >> 12;
        own[i] = i < 4 ? 8 * RP + slots + p.q : (p.ht ? RP + S_HELP_W + (p.q >> 3) : 0);
        if (i < r) start += own[i];
        total += own[i];
      }
      const uint32_t np = TPH - total;
      const uint32_t n1 = TPH - p.ht;
      uint32_t p1o = 0, p1n = 0;
#pragma unroll
      for (int i = 0; i < 5; i++) {
        const uint32_t cnt = i < 4 ? ((n1 + i) >> 2) - own[i] : p.ht - own[4];
        if (i < r) p1o += cnt;
        if (i == r) p1n = cnt;
      }
      const uint32_t h2 = p.ht ? p.h2 + (h < 12 ? 6 : 0) : 0, n2 = np - h2;
      const uint32_t p2n = helper ? h2 : (n2 + r) >> 2;
      uint32_t p2o = 0;
#pragma unroll
      for (int i = 0; i < 4; i++) if (i < r) p2o += (n2 + i) >> 2;
      const uint32_t hb = h * TPH, base = hb + start, zone = hb + total;
      uint32_t ctr, qf, st0, pk, rt, keep;
      if (!helper) {
        const uint32_t ns = (sb + SMEM_BYTES - side) >> 12;
        rt = base + w * RP;
        st0 = base + 8 * RP + w;
        pk = w | (8u << 8) | (8u << 16) | (((ns - w + 7) >> 3) << 24);
        keep = base + 8 * RP + ns;
        ctr = sb + OFF_CTR;
        qf = sb + OFF_QF;
      } else {
        rt = base;
        st0 = base + RP;
        pk = (w * S_HELP_W) | (1u << 8) | (1u << 16) | ((uint32_t)S_HELP_W << 24);
        keep = base + RP + S_HELP_W;
        ctr = sb + OFF_CTR + w * 4;
        qf = sb + OFF_QF_HELP + w * 512;
      }
      const uint32_t wp = sb + OFF_WP + w * 32;
      const uint32_t seg = helper ? side + 8 * S_HELP_W * 4096 + w * 128 : sb + OFF_SEG;
      sts32(wp, seg); sts32(wp + 4, ctr);
      sts32(wp + 16, qf); sts32(wp + 20, st0); sts32(wp + 24, pk); sts32(wp + 28, rt);
      if (helper || w == 0) {
        auto blk = [&](int i, uint32_t lim, uint32_t base_d, uint32_t pf, uint32_t cnt) {
          sts32(seg + i * 16, lim); sts32(seg + i * 16 + 4, base_d); sts32(seg + i * 16 + 8, pf); sts32(seg + i * 16 + 12, cnt);
        };
        const uint32_t t0 = p1n, t1 = t0 + q, t2 = t1 + p1n, t3 = t2 + q, t4 = t3 + p2n, t5 = t4 + p2n;
        blk(0, t0, (D_VALID | D_B0) + zone + p1o, 0xffffffffu, 0);
        blk(1, t1, (D_VALID | D_B0) + keep - t0, 0, 0);
        blk(2, t2, (D_VALID | D_B1 | D_PAST0) + zone + p1o + TPB - t1, 0xffffffffu, 0);
        blk(3, t3, (D_VALID | D_B1 | D_PAST0) + keep + TPB - t2, 0, 0);
        blk(4, t4, (D_VALID | D_B0 | D_N0 | D_PAST0 | D_PAST1) + zone + p2o - t3, 0xffffffffu, 0);
        blk(5, t5, (D_VALID | D_B1 | D_N1 | D_PASTS) + zone + p2o + TPB - t4, 0xffffffffu, 0);
        blk(6, 0, 0, 0xffffffffu, 0);
        blk(7, q, keep + q - 1, 0, ctr + 32);
      }
      for (int s = 0; s < 4; s++) mbar_init(sb + OFF_RBAR + (w * 4 + s) * 8, 1);
      for (int s = w; s < 40; s += 8) mbar_init(sb + OFF_SBAR + s * 8, 1);
    }
  } else {
    if (!helper) aux_fill_wq(p, sb, tid - 256, c);
    if (w == 8) {
      if (lane < 24) sts32(sb + OFF_CTR + lane * 4, 0);
      if (lane == 0) {
        mbar_init(sb + BAR_Q1, 1); mbar_init(sb + BAR_R0, 1); mbar_init(sb + BAR_R1, 1);
        for (int k = 0; k < 4; k++) mbar_init(sb + BAR_P0 + 8 * k, 8);
      }
    }
  }
  asm volatile("fence.mbarrier_init.release.cluster;" ::: "memory");
  asm volatile("fence.proxy.async.shared::cta;" ::: "memory");
  __syncthreads();

  if (w < 8) {
    stream_prologue(&tmK, &tmV, sb, side, w, lane);
    asm volatile("setmaxnreg.inc.sync.aligned.u32 %0;" ::"n"(REG_STREAM));
    int lane2;
    asm volatile("mov.u32 %0, %%laneid;" : "=r"(lane2));
    stream_warp(&tmK, &tmV, sb, side, w, lane2, p);
  } else {
    uint32_t epoch;
    asm volatile("ld.relaxed.gpu.global.u32 %0, [%1];" : "=r"(epoch) : "l"(&g_epoch) : "memory");
    epoch += 1;
    if (!helper) aux_init_main(p, sb, tid - 256, c, ll_tag(epoch, 0));
    asm volatile("setmaxnreg.dec.sync.aligned.u32 %0;" ::"n"(REG_AUX));
    int t;
    asm volatile("mov.u32 %0, %%tid.x;" : "=r"(t));
    t -= 256;
    if (!helper) aux_main(p, sb, t, c, epoch);
    else aux_helper(sb, t, c - NMAIN, epoch);
    if (c == 0 && t == 0) asm volatile("st.relaxed.gpu.global.u32 [%0], %1;" ::"l"(&g_epoch), "r"(epoch) : "memory");
  }
}

typedef CUresult (*EncodeTiledFn)(CUtensorMap*, CUtensorMapDataType, cuuint32_t, void*, const cuuint64_t*,
                                  const cuuint64_t*, const cuuint32_t*, const cuuint32_t*, CUtensorMapInterleave,
                                  CUtensorMapSwizzle, CUtensorMapL2promotion, CUtensorMapFloatOOBfill);

}

extern "C" void kernel_launch(void* const* d_in, const int* in_sizes, int n_in, void* d_out, int out_size) {
  (void)in_sizes; (void)n_in; (void)out_size;
  static EncodeTiledFn encode = nullptr;
  static int sms = 0;
  if (!encode) {
    void* fn = nullptr;
    cudaDriverEntryPointQueryResult qr;
    cudaGetDriverEntryPoint("cuTensorMapEncodeTiled", &fn, cudaEnableDefault, &qr);
    encode = (EncodeTiledFn)fn;
    int dev = 0;
    cudaGetDevice(&dev);
    cudaDeviceGetAttribute(&sms, cudaDevAttrMultiProcessorCount, dev);
    cudaFuncSetAttribute(fused_decode_kernel, cudaFuncAttributeMaxDynamicSharedMemorySize, SMEM_BYTES);
  }
  CUtensorMap tmK, tmV;
  const cuuint64_t gdim[2] = {64, (cuuint64_t)2 * NH * SK * 2};
  const cuuint64_t gstr[1] = {128};
  const cuuint32_t box[2] = {64, 16};
  const cuuint32_t estr[2] = {1, 1};
  encode(&tmK, CU_TENSOR_MAP_DATA_TYPE_BFLOAT16, 2, d_in[1], gdim, gstr, box, estr, CU_TENSOR_MAP_INTERLEAVE_NONE,
         CU_TENSOR_MAP_SWIZZLE_128B, CU_TENSOR_MAP_L2_PROMOTION_NONE, CU_TENSOR_MAP_FLOAT_OOB_FILL_NONE);
  encode(&tmV, CU_TENSOR_MAP_DATA_TYPE_BFLOAT16, 2, d_in[2], gdim, gstr, box, estr, CU_TENSOR_MAP_INTERLEAVE_NONE,
         CU_TENSOR_MAP_SWIZZLE_128B, CU_TENSOR_MAP_L2_PROMOTION_NONE, CU_TENSOR_MAP_FLOAT_OOB_FILL_NONE);
  Params p;
  p.x = (const __nv_bfloat16*)d_in[0];
  p.wq = (const __nv_bfloat16*)d_in[3];
  p.wo = (const __nv_bfloat16*)d_in[4];
  p.wg = (const __nv_bfloat16*)d_in[6];
  p.wu = (const __nv_bfloat16*)d_in[7];
  p.wd = (const __nv_bfloat16*)d_in[8];
  p.out = (__nv_bfloat16*)d_out;
  const bool helpers = sms >= NMAIN + NHELP;
  p.ht = helpers ? HELP_P1 : 0;
  p.h2 = HELP_P2;
  p.q = KEEP_L2;
  p.zero = 0;
  p.kbytes = (const uint8_t*)d_in[1];
  p.vbytes = (const uint8_t*)d_in[2];
  fused_decode_kernel<<<helpers ? NMAIN + NHELP : NMAIN, 384, SMEM_BYTES, cudaStreamPerThread>>>(tmK, tmV, p);
}
```
